```python
import torch

def _softmax(x, axis=-1):
    return torch.softmax(x, dim=axis)
def _gelu(x):
    return torch.nn.functional.gelu(x, approximate="tanh")
def _silu(x):
    return torch.nn.functional.silu(x)
def _sigmoid(x):
    return torch.sigmoid(x)
def _layernorm(x, axis=-1, eps=1e-5):
    m = x.mean(dim=axis, keepdim=True)
    v = x.var(dim=axis, keepdim=True, unbiased=False)
    return (x - m) / torch.sqrt(v + eps)
def _scatter_add(tgt, idx, src, axis=0):
    return tgt.clone().index_add_(axis, idx, src)
def _segment_sum(src, seg, n):
    out = torch.zeros((n,) + src.shape[1:], dtype=src.dtype)
    return out.index_add_(0, seg, src)
def _pad(x, pw):
    flat = tuple(v for pair in reversed(pw) for v in pair)
    return torch.nn.functional.pad(x, flat)

kernel_name = 'gated_mix__ssm_conv_s5__swiglu_ffn__prompt'

def setup_inputs():

    _w = (lambda a: (lambda t: t.to(torch.bfloat16) if t.is_floating_point() else t)(torch.as_tensor(a)))
    def _A_setup():
        B, S, D = 1, 2048, 640
        P = D
        Lambda_re = -0.5 * (lambda _x: torch.exp(torch.as_tensor(_x)))((lambda *s: torch.randn(*s, dtype=torch.bfloat16) * 0.2)(P))
        Lambda_im = (lambda *s: torch.randn(*s, dtype=torch.bfloat16) * 0.4)(P) * 1.0
        B_re = (lambda *s: torch.randn(*s, dtype=torch.bfloat16) * 0.2)(P, D) * (D ** -0.5)
        B_im = (lambda *s: torch.randn(*s, dtype=torch.bfloat16) * 0.2)(P, D) * (D ** -0.5)
        C_re = (lambda *s: torch.randn(*s, dtype=torch.bfloat16) * 0.2)(D, P) * (P ** -0.5)
        C_im = (lambda *s: torch.randn(*s, dtype=torch.bfloat16) * 0.2)(D, P) * (P ** -0.5)
        log_dt = (lambda *s: torch.randn(*s, dtype=torch.bfloat16) * 0.2)(P) * 0.3 - 2.0
        Dskip = (lambda *s: torch.randn(*s, dtype=torch.bfloat16) * 0.05)(D)
        return {
            "x": _w((lambda *s: torch.randn(*s, dtype=torch.bfloat16) * 0.05)(B, S, D)),
            "Lambda_re": _w(Lambda_re),
            "Lambda_im": _w(Lambda_im),
            "B_re": _w(B_re),
            "B_im": _w(B_im),
            "C_re": _w(C_re),
            "C_im": _w(C_im),
            "log_dt": _w(log_dt),
            "Dskip": _w(Dskip),
        }
    _A_in = _A_setup()

    def _B_setup():
        B, S, D, F = 1, 2048, 640, 1728
        return {
            "x": _w((lambda *s: torch.randn(*s, dtype=torch.bfloat16) * 0.05)(B, S, D)),
            "w_gate": _w((lambda *s: torch.randn(*s, dtype=torch.bfloat16) * 0.05)(D, F)),
            "w_up": _w((lambda *s: torch.randn(*s, dtype=torch.bfloat16) * 0.05)(D, F)),
            "w_down": _w((lambda *s: torch.randn(*s, dtype=torch.bfloat16) * 0.05)(F, D)),
        }
    _B_in = _B_setup()

    return {
        "A_x": _A_in["x"],
        "A_Lambda_re": _A_in["Lambda_re"],
        "A_Lambda_im": _A_in["Lambda_im"],
        "A_B_re": _A_in["B_re"],
        "A_B_im": _A_in["B_im"],
        "A_C_re": _A_in["C_re"],
        "A_C_im": _A_in["C_im"],
        "A_log_dt": _A_in["log_dt"],
        "A_Dskip": _A_in["Dskip"],
        "B_x": _B_in["x"],
        "B_w_gate": _B_in["w_gate"],
        "B_w_up": _B_in["w_up"],
        "B_w_down": _B_in["w_down"],
        "gate_w": _w((lambda *s: torch.randn(*s, dtype=torch.bfloat16) * 0.05)(640) * 16.0),
    }

def reference(A_x, A_Lambda_re, A_Lambda_im, A_B_re, A_B_im, A_C_re, A_C_im, A_log_dt, A_Dskip, B_x, B_w_gate, B_w_up, B_w_down, gate_w):
    def _A_ref(x, Lambda_re, Lambda_im, B_re, B_im, C_re, C_im, log_dt, Dskip):
        Bsz, L, H = x.shape
        Lam = Lambda_re + 1j * Lambda_im
        Bmat = B_re + 1j * B_im
        Cmat = C_re + 1j * C_im
        dt = torch.exp(log_dt)
        Lam_bar = torch.exp(dt * Lam)
        B_bar = ((Lam_bar - 1.0) / Lam)[:, None] * Bmat
        Bu = torch.einsum("bld,pd->blp", x + 0j, B_bar)
        h = torch.zeros_like(Bu[:, 0, :])
        hs = []
        for t in range(L):
            h = Lam_bar[None, :] * h + Bu[:, t, :]
            hs.append(h)
        hseq = torch.stack(hs, 1)
        y = 2.0 * torch.einsum("blp,dp->bld", hseq, Cmat).real + x * Dskip[None, None, :]
        return y

    def _B_ref(x, w_gate, w_up, w_down):
        g = _silu(x @ w_gate)
        u = x @ w_up
        return (g * u) @ w_down

    x = A_x
    g = _sigmoid((x * gate_w).sum(-1, keepdims=True))
    a = _A_ref(x, A_Lambda_re, A_Lambda_im, A_B_re, A_B_im, A_C_re, A_C_im, A_log_dt, A_Dskip)
    b = _B_ref(x, B_w_gate, B_w_up, B_w_down)
    return g * a + (1 - g) * b
```

```cpp
#include <cuda_runtime.h>
#include <cuda.h>
#include <cuda_bf16.h>
#include <stdint.h>

namespace {

constexpr int L_ = 2048, D_ = 640, F_ = 1728;
#define HP 2048
constexpr int NCTA = 132;
constexpr int XB = 16384;
constexpr int SM_RING = 10 * XB;
constexpr int SM_MISC = 14 * XB;
constexpr int SLOT2 = 36864;
constexpr int NS2 = 5;
constexpr int SM_XCH = NS2 * SLOT2;
constexpr int SMEM_BYTES = SM_MISC + 3072;
#define LEAD 4
#define TLR 0
#define AGG_DELAY 300
#define NFB 8
#define PF1 4
constexpr int B_XFULL = 0;
constexpr int B_FULL1 = 80;
constexpr int B_EMPTY1 = 112;
constexpr int B_FULL2 = 144;
constexpr int B_EMPTY2 = 184;
constexpr int B_XCH = 224;
constexpr int B_PUB = 288;
constexpr int B_XFREE = 328;
constexpr int B_GREADY = 336;
constexpr int B_ORDER = 344;
constexpr int B_EPOCH = 352;
constexpr int B_DONE = 360;
constexpr int B_PAR = 368;
constexpr int B_LEAD = 376;
constexpr int M_EPOCH = 2944;
constexpr int M_NREADY = 2948;
constexpr int M_G = 384;
constexpr int M_PAR = 896;

struct Params {
  CUtensorMap x, bre, bim, wg, wu, ht, c[2], wd;
  const __nv_bfloat16 *px, *lre, *lim, *ldt, *dskip, *gw, *pbre, *pbim, *pcre, *pcim, *pwg, *pwu, *pwd;
  float* out;
  uint32_t zero;
};

__device__ __nv_bfloat16 g_ht[3008 * HP];
__device__ uint4 g_agg[16 * 320];
__device__ uint2 g_gate[2048];
__device__ unsigned g_cnt[16 * 64];
__device__ unsigned long long g_ticket;
#define TLP(c, i)

#define TL_ARG
#define TL_PASS
template <int TA, int TB>
__device__ __forceinline__ void wgmma_n128(float (&d)[64], uint64_t da, uint64_t db, int sc) {
  asm volatile("{\n.reg .pred p;\nsetp.ne.b32 p, %66, 0;\n"
    "wgmma.mma_async.sync.aligned.m64n128k16.f32.bf16.bf16 {%0,%1,%2,%3,%4,%5,%6,%7,%8,%9,%10,%11,%12,%13,%14,%15,%16,%17,%18,%19,%20,%21,%22,%23,%24,%25,%26,%27,%28,%29,%30,%31,%32,%33,%34,%35,%36,%37,%38,%39,%40,%41,%42,%43,%44,%45,%46,%47,%48,%49,%50,%51,%52,%53,%54,%55,%56,%57,%58,%59,%60,%61,%62,%63}, %64, %65, p, 1, 1, %67, %68;\n}\n"
    : "+f"(d[0]),"+f"(d[1]),"+f"(d[2]),"+f"(d[3]),"+f"(d[4]),"+f"(d[5]),"+f"(d[6]),"+f"(d[7]),"+f"(d[8]),"+f"(d[9]),"+f"(d[10]),"+f"(d[11]),"+f"(d[12]),"+f"(d[13]),"+f"(d[14]),"+f"(d[15]),"+f"(d[16]),"+f"(d[17]),"+f"(d[18]),"+f"(d[19]),"+f"(d[20]),"+f"(d[21]),"+f"(d[22]),"+f"(d[23]),"+f"(d[24]),"+f"(d[25]),"+f"(d[26]),"+f"(d[27]),"+f"(d[28]),"+f"(d[29]),"+f"(d[30]),"+f"(d[31]),"+f"(d[32]),"+f"(d[33]),"+f"(d[34]),"+f"(d[35]),"+f"(d[36]),"+f"(d[37]),"+f"(d[38]),"+f"(d[39]),"+f"(d[40]),"+f"(d[41]),"+f"(d[42]),"+f"(d[43]),"+f"(d[44]),"+f"(d[45]),"+f"(d[46]),"+f"(d[47]),"+f"(d[48]),"+f"(d[49]),"+f"(d[50]),"+f"(d[51]),"+f"(d[52]),"+f"(d[53]),"+f"(d[54]),"+f"(d[55]),"+f"(d[56]),"+f"(d[57]),"+f"(d[58]),"+f"(d[59]),"+f"(d[60]),"+f"(d[61]),"+f"(d[62]),"+f"(d[63])
    : "l"(da), "l"(db), "r"(sc), "n"(TA), "n"(TB));
}
template <int TA, int TB>
__device__ __forceinline__ void wgmma_n160(float (&d)[80], uint64_t da, uint64_t db, int sc) {
  asm volatile("{\n.reg .pred p;\nsetp.ne.b32 p, %82, 0;\n"
    "wgmma.mma_async.sync.aligned.m64n160k16.f32.bf16.bf16 {%0,%1,%2,%3,%4,%5,%6,%7,%8,%9,%10,%11,%12,%13,%14,%15,%16,%17,%18,%19,%20,%21,%22,%23,%24,%25,%26,%27,%28,%29,%30,%31,%32,%33,%34,%35,%36,%37,%38,%39,%40,%41,%42,%43,%44,%45,%46,%47,%48,%49,%50,%51,%52,%53,%54,%55,%56,%57,%58,%59,%60,%61,%62,%63,%64,%65,%66,%67,%68,%69,%70,%71,%72,%73,%74,%75,%76,%77,%78,%79}, %80, %81, p, 1, 1, %83, %84;\n}\n"
    : "+f"(d[0]),"+f"(d[1]),"+f"(d[2]),"+f"(d[3]),"+f"(d[4]),"+f"(d[5]),"+f"(d[6]),"+f"(d[7]),"+f"(d[8]),"+f"(d[9]),"+f"(d[10]),"+f"(d[11]),"+f"(d[12]),"+f"(d[13]),"+f"(d[14]),"+f"(d[15]),"+f"(d[16]),"+f"(d[17]),"+f"(d[18]),"+f"(d[19]),"+f"(d[20]),"+f"(d[21]),"+f"(d[22]),"+f"(d[23]),"+f"(d[24]),"+f"(d[25]),"+f"(d[26]),"+f"(d[27]),"+f"(d[28]),"+f"(d[29]),"+f"(d[30]),"+f"(d[31]),"+f"(d[32]),"+f"(d[33]),"+f"(d[34]),"+f"(d[35]),"+f"(d[36]),"+f"(d[37]),"+f"(d[38]),"+f"(d[39]),"+f"(d[40]),"+f"(d[41]),"+f"(d[42]),"+f"(d[43]),"+f"(d[44]),"+f"(d[45]),"+f"(d[46]),"+f"(d[47]),"+f"(d[48]),"+f"(d[49]),"+f"(d[50]),"+f"(d[51]),"+f"(d[52]),"+f"(d[53]),"+f"(d[54]),"+f"(d[55]),"+f"(d[56]),"+f"(d[57]),"+f"(d[58]),"+f"(d[59]),"+f"(d[60]),"+f"(d[61]),"+f"(d[62]),"+f"(d[63]),"+f"(d[64]),"+f"(d[65]),"+f"(d[66]),"+f"(d[67]),"+f"(d[68]),"+f"(d[69]),"+f"(d[70]),"+f"(d[71]),"+f"(d[72]),"+f"(d[73]),"+f"(d[74]),"+f"(d[75]),"+f"(d[76]),"+f"(d[77]),"+f"(d[78]),"+f"(d[79])
    : "l"(da), "l"(db), "r"(sc), "n"(TA), "n"(TB));
}

#define ELECT "{\n.reg .pred e;\nelect.sync _|e, 0xffffffff;\n@e "
__device__ __forceinline__ void mbar_init(uint32_t b, int c) { asm volatile("mbarrier.init.shared::cta.b64 [%0], %1;" ::"r"(b), "r"(c)); }
__device__ __forceinline__ void mbar_expect(uint32_t b, int bytes) { asm volatile(ELECT "mbarrier.arrive.expect_tx.shared::cta.b64 _, [%0], %1;\n}" ::"r"(b), "r"(bytes) : "memory"); }
__device__ __forceinline__ void mbar_arrive(uint32_t b) { asm volatile("mbarrier.arrive.shared::cta.b64 _, [%0];" ::"r"(b) : "memory"); }
__device__ __forceinline__ void mbar_arrive2(uint32_t b) { asm volatile("mbarrier.arrive.shared::cta.b64 _, [%0], 2;" ::"r"(b) : "memory"); }
__device__ __forceinline__ void mbar_arrive_remote(uint32_t cluster_addr) { asm volatile("mbarrier.arrive.shared::cluster.b64 _, [%0];" ::"r"(cluster_addr) : "memory"); }
__device__ __forceinline__ uint32_t mapa(uint32_t a, uint32_t cta) { uint32_t r; asm("mapa.shared::cluster.u32 %0, %1, %2;" : "=r"(r) : "r"(a), "r"(cta)); return r; }
__device__ __forceinline__ void mbar_wait(uint32_t b, uint32_t parity) {
  asm volatile("{\n.reg .pred p;\nW: mbarrier.try_wait.parity.shared::cta.b64 p, [%0], %1;\n@!p bra W;\n}\n" ::"r"(b), "r"(parity) : "memory");
}
__device__ __forceinline__ void mbar_wait_cluster(uint32_t b, uint32_t parity) {
  asm volatile("{\n.reg .pred p;\nW: mbarrier.try_wait.parity.acquire.cluster.shared::cta.b64 p, [%0], %1;\n@!p bra W;\n}\n" ::"r"(b), "r"(parity) : "memory");
}
__device__ __forceinline__ void mbar_spin_bounded(uint32_t b, uint32_t parity) {
  asm volatile(
      "{\n.reg .pred p;\n.reg .u32 c;\nmov.u32 c, 0;\n"
      "W: mbarrier.try_wait.parity.shared::cta.b64 p, [%0], %1;\n"
      "@p bra D;\n"
      "add.u32 c, c, 1;\nsetp.lt.u32 p, c, 0x1000000;\n@p bra W;\ntrap;\n"
      "D:\n}\n" ::"r"(b), "r"(parity) : "memory");
}
__device__ __forceinline__ void mbar_wait_bounded(uint32_t b, uint32_t parity) {
  asm volatile(
      "{\n.reg .pred p;\n.reg .u32 c;\nmov.u32 c, 0;\n"
      "W: mbarrier.try_wait.parity.shared::cta.b64 p, [%0], %1, 1000;\n"
      "@p bra D;\n"
      "add.u32 c, c, 1;\nsetp.lt.u32 p, c, 0x400000;\n@p bra W;\ntrap;\n"
      "D:\n}\n" ::"r"(b), "r"(parity) : "memory");
}
__device__ __forceinline__ void tma2(uint32_t dst, const CUtensorMap* m, uint32_t bar, int c0, int c1) {
  asm volatile(ELECT "cp.async.bulk.tensor.2d.shared::cluster.global.mbarrier::complete_tx::bytes [%0], [%1, {%3,%4}], [%2];\n}"
               ::"r"(dst), "l"(m), "r"(bar), "r"(c0), "r"(c1) : "memory");
}
__device__ __forceinline__ void tma2_mc(uint32_t dst, const CUtensorMap* m, uint32_t bar, int c0, int c1) {
  asm volatile(ELECT "cp.async.bulk.tensor.2d.shared::cluster.global.mbarrier::complete_tx::bytes.multicast::cluster [%0], [%1, {%3,%4}], [%2], %5;\n}"
               ::"r"(dst), "l"(m), "r"(bar), "r"(c0), "r"(c1), "h"((uint16_t)3) : "memory");
}
__device__ __forceinline__ void tma3(uint32_t dst, const CUtensorMap* m, uint32_t bar, int c0, int c1, int c2) {
  asm volatile(ELECT "cp.async.bulk.tensor.3d.shared::cluster.global.mbarrier::complete_tx::bytes [%0], [%1, {%3,%4,%5}], [%2];\n}"
               ::"r"(dst), "l"(m), "r"(bar), "r"(c0), "r"(c1), "r"(c2) : "memory");
}
__device__ __forceinline__ void tma5(uint32_t dst, const CUtensorMap* m, uint32_t bar, int c0, int c1, int c2, int c3, int c4) {
  asm volatile(ELECT "cp.async.bulk.tensor.5d.shared::cluster.global.mbarrier::complete_tx::bytes [%0], [%1, {%3,%4,%5,%6,%7}], [%2];\n}"
               ::"r"(dst), "l"(m), "r"(bar), "r"(c0), "r"(c1), "r"(c2), "r"(c3), "r"(c4) : "memory");
}
__device__ __forceinline__ void tma2_pf(const CUtensorMap* m, int c0, int c1) {
  asm volatile(ELECT "cp.async.bulk.prefetch.tensor.2d.L2.global [%0, {%1,%2}];\n}" ::"l"(m), "r"(c0), "r"(c1) : "memory");
}
__device__ __forceinline__ void tma5_pf(const CUtensorMap* m, int c0, int c4) {
  asm volatile(ELECT "cp.async.bulk.prefetch.tensor.5d.L2.global [%0, {%1,%2,%2,%2,%3}];\n}" ::"l"(m), "r"(c0), "r"(0), "r"(c4) : "memory");
}
__device__ __forceinline__ void l2_prefetch(const void* p) { asm volatile("prefetch.global.L2 [%0];" ::"l"(p)); }
__device__ __forceinline__ uint64_t desc(uint32_t addr, uint32_t lbo) {
  return (uint64_t)((addr & 0x3FFFF) >> 4) | ((uint64_t)(lbo >> 4) << 16) | (64ull << 32) | (1ull << 62);
}
__device__ __forceinline__ uint32_t dlo(uint32_t addr, uint32_t lbo) { return ((addr & 0x3FFFF) >> 4) | ((lbo >> 4) << 16); }
__device__ __forceinline__ uint64_t d64(uint32_t lo) { return (uint64_t)lo | (0x40000040ull << 32); }
__device__ __forceinline__ void arrive_if(uint32_t b, bool p) {
  asm volatile("{\n.reg .pred p;\nsetp.ne.b32 p, %1, 0;\n@p mbarrier.arrive.shared::cta.b64 _, [%0];\n}\n" ::"r"(b), "r"((int)p) : "memory");
}
__device__ __forceinline__ void arrive_cluster_if(uint32_t cluster_addr, bool p) {
  asm volatile("{\n.reg .pred p;\nsetp.ne.b32 p, %1, 0;\n@p mbarrier.arrive.shared::cluster.b64 _, [%0];\n}\n" ::"r"(cluster_addr), "r"((int)p) : "memory");
}
__device__ __forceinline__ int uni(int v) { return (int)__reduce_max_sync(~0u, (unsigned)v); }
__device__ __forceinline__ void wg_fence() { asm volatile("wgmma.fence.sync.aligned;" ::: "memory"); }
__device__ __forceinline__ void wg_commit() { asm volatile("wgmma.commit_group.sync.aligned;" ::: "memory"); }
template <int N> __device__ __forceinline__ void wg_wait() { asm volatile("wgmma.wait_group.sync.aligned %0;" ::"n"(N) : "memory"); }
template <int N> __device__ __forceinline__ void keep(float (&d)[N]) {
#pragma unroll
  for (int i = 0; i < N; i++) asm volatile("" : "+f"(d[i])::"memory");
}
__device__ __forceinline__ uint32_t pack_bf16(float lo, float hi) { uint32_t r; asm("cvt.rn.bf16x2.f32 %0, %1, %2;" : "=r"(r) : "f"(hi), "f"(lo)); return r; }
__device__ __forceinline__ float bf16r(float v) { return __bfloat162float(__float2bfloat16_rn(v)); }
__device__ __forceinline__ float lds_f(uint32_t a) { float v; asm volatile("ld.shared.f32 %0, [%1];" : "=f"(v) : "r"(a)); return v; }
__device__ __forceinline__ float4 lds_f4(uint32_t a) { float4 v; asm volatile("ld.shared.v4.f32 {%0,%1,%2,%3}, [%4];" : "=f"(v.x), "=f"(v.y), "=f"(v.z), "=f"(v.w) : "r"(a)); return v; }
__device__ __forceinline__ void stg4(void* p, uint32_t a, uint32_t b, uint32_t c, uint32_t d) {
  asm volatile("st.global.v4.b32 [%0], {%1,%2,%3,%4};" ::"l"(p), "r"(a), "r"(b), "r"(c), "r"(d) : "memory");
}
struct cf { float r, i; };
__device__ __forceinline__ cf cmul(cf a, cf b) { return {a.r * b.r - a.i * b.i, a.r * b.i + a.i * b.r}; }
__device__ __forceinline__ cf cfma(cf a, cf b, cf c) { return {fmaf(-a.i, b.i, fmaf(a.r, b.r, c.r)), fmaf(a.i, b.r, fmaf(a.r, b.i, c.i))}; }

template <bool SSM>
__device__ __forceinline__ void mainloop1(float (&a0)[64], float (&a1)[64], uint32_t sb, int rnd, uint32_t rel, bool swap, int lane TL_ARG) {
  const uint32_t bars = sb + SM_MISC;
  rnd = uni(rnd);
  if (!SSM) swap = uni(swap);
  if (rnd > 0) mbar_wait(bars + B_ORDER, (rnd - 1) & 1);
  const bool releaser = lane < 2;
  const uint32_t dbase = (sb & 0x3FFFF) >> 4;
  int it = rnd * 10;
#pragma unroll 1
  for (int kb = 0; kb < 10; kb++, it++) {
    const uint32_t slot = it & 3;
    uint32_t dw = dbase + (SM_RING >> 4) + slot * (XB >> 4), dx = dbase + kb * (XB >> 4);
    if (!SSM && swap) { const uint32_t t = dw; dw = dx; dx = t; }
    dx |= 1u << 16;
    dw |= 1u << 16;
    if (rnd < 2) mbar_wait(bars + B_XFULL + kb * 8, 0);
    mbar_wait(bars + B_FULL1 + slot * 8, (it >> 2) & 1);
    wg_fence();
#pragma unroll
    for (int kk = 0; kk < 4; kk++) {
      const int sc = (kb | kk) != 0;
      if (SSM) {
        wgmma_n128<0, 0>(a0, d64(dw + kk * 2), d64(dx + kk * 2), sc);
        wgmma_n128<0, 0>(a1, d64(dw + 512 + kk * 2), d64(dx + kk * 2), sc);
      } else {
        wgmma_n128<1, 0>(a0, d64(dw + kk * 128), d64(dx + kk * 2), sc);
        wgmma_n128<1, 0>(a1, d64(dw + 512 + kk * 128), d64(dx + kk * 2), sc);
      }
    }
    wg_commit();
    wg_wait<1>();
    arrive_cluster_if(rel + ((it - 1) & 3) * 8, releaser && kb > 0);
  }
  arrive_if(bars + B_ORDER, lane == 0);
  wg_wait<0>();
  keep(a0);
  keep(a1);
  arrive_cluster_if(rel + ((it - 1) & 3) * 8, releaser);
}

__device__ __forceinline__ void ffn_epilogue(float (&ag)[64], float (&au)[64], int rb, int u0, int lane) {
  __nv_bfloat16* dst = g_ht + (size_t)(1280 + u0) * HP + rb * 128 + 8 * (lane & 3);
#pragma unroll
  for (int hi = 0; hi < 2; hi++)
#pragma unroll
    for (int k = 0; k < 4; k++) {
      uint32_t pk[4];
#pragma unroll
      for (int b = 0; b < 4; b++) {
        float v[2];
#pragma unroll
        for (int e = 0; e < 2; e++) {
          const int x = 4 * (4 * k + b) + 2 * hi + e;
          const float hz = 0.5f * ag[x], pu = hz * au[x];
          float th;
          asm("tanh.approx.f32 %0, %1;" : "=f"(th) : "f"(hz));
          v[e] = fmaf(pu, th, pu);
        }
        pk[b] = pack_bf16(v[0], v[1]);
      }
      stg4(dst + (size_t)(8 * hi) * HP + 32 * k, pk[0], pk[1], pk[2], pk[3]);
    }
}

struct ChanPar { cf lam[2], coef[2], l32[2]; };
__device__ __forceinline__ float4 chan_params(float lr, float li, float ldt) {
  const float dt = bf16r(expf(ldt));
  const float e = expf(dt * lr);
  float s, co;
  sincosf(dt * li, &s, &co);
  const float nr = e * co - 1.f, ni = e * s;
  const bool big = fabsf(lr) >= fabsf(li);
  const float a = big ? lr : li, b = big ? li : lr, t = b / a, inv = 2.f / (a + b * t);
  return make_float4(e * co, ni, (big ? nr + ni * t : nr * t + ni) * inv, (big ? ni - nr * t : ni * t - nr) * inv);
}

__device__ __forceinline__ cf shfl_up4(cf v, int d) { return {__shfl_up_sync(~0u, v.r, d, 4), __shfl_up_sync(~0u, v.i, d, 4)}; }
__device__ __forceinline__ cf shfl_dn4(cf v, int d) { return {__shfl_down_sync(~0u, v.r, d, 4), __shfl_down_sync(~0u, v.i, d, 4)}; }

__device__ __forceinline__ uint32_t hmul2(uint32_t a, uint32_t b) { uint32_t r; asm("mul.rn.bf16x2 %0, %1, %2;" : "=r"(r) : "r"(a), "r"(b)); return r; }
__device__ __forceinline__ uint32_t hfma2(uint32_t a, uint32_t b, uint32_t c) { uint32_t r; asm("fma.rn.bf16x2 %0, %1, %2, %3;" : "=r"(r) : "r"(a), "r"(b), "r"(c)); return r; }
__device__ __forceinline__ cf after(cf v, float dep, uint32_t zero) {
  const uint32_t m = __float_as_uint(dep) & zero;
  return {__uint_as_float(__float_as_uint(v.r) | m), __uint_as_float(__float_as_uint(v.i) | m)};
}
__device__ __forceinline__ uint64_t tag_state(cf v, uint32_t tag) {
  return ((uint64_t)((__float_as_uint(v.i) & ~31u) | ((tag >> 5) & 31u)) << 32) | ((__float_as_uint(v.r) & ~31u) | (tag & 31u));
}
__device__ __forceinline__ bool ld_aggs(uint64_t (&v)[4][2], const uint4* src, int n, uint64_t tg) {
  uint64_t bad = 0;
#pragma unroll
  for (int u = 0; u < 4; u++) {
    v[u][0] = v[u][1] = tg;
    asm volatile("{\n.reg .pred p;\nsetp.gt.s32 p, %3, 0;\n@p ld.relaxed.gpu.global.v2.b64 {%0,%1}, [%2];\n}\n"
                 : "+l"(v[u][0]), "+l"(v[u][1]) : "l"(src - u * 320), "r"(n - u) : "memory");
  }
#pragma unroll
  for (int u = 0; u < 4; u++) bad |= (v[u][0] ^ tg) | (v[u][1] ^ tg);
  return (bad & 0x1f0000001full) == 0;
}

__device__ __forceinline__ void ssm_epilogue(float (&ar)[64], float (&ai)[64], const ChanPar& cp, int rb, int c0, int lane, uint32_t tag, uint32_t zero TL_ARG) {
  const int q = lane & 3;
  cf h[2], e[2], l64[2];
#pragma unroll
  for (int hi = 0; hi < 2; hi++) h[hi] = {ar[2 * hi], ai[2 * hi]};
#pragma unroll
  for (int i = 1; i < 32; i++)
#pragma unroll
    for (int hi = 0; hi < 2; hi++) {
      const int x = 4 * (i >> 1) + 2 * hi + (i & 1);
      h[hi] = cfma(cp.lam[hi], h[hi], {ar[x], ai[x]});
    }
#pragma unroll
  for (int hi = 0; hi < 2; hi++) {
    l64[hi] = cmul(cp.l32[hi], cp.l32[hi]);
    cf t = shfl_up4(h[hi], 1);
    if (q >= 1) h[hi] = cfma(cp.l32[hi], t, h[hi]);
    t = shfl_up4(h[hi], 2);
    if (q >= 2) h[hi] = cfma(l64[hi], t, h[hi]);
  }
  const int rec = (c0 >> 4) * 8 + (c0 & 7);
  if (q == 3 && rb < 15)
    asm volatile("st.relaxed.gpu.global.v2.b64 [%0], {%1,%2};" ::"l"(g_agg + rb * 320 + rec), "l"(tag_state(h[0], tag)), "l"(tag_state(h[1], tag)) : "memory");
  TLP(threadIdx.x == 0, 49);
  cf l128[2], l512[2], l1024[2];
#pragma unroll
  for (int hi = 0; hi < 2; hi++) {
    const cf t = shfl_up4(h[hi], 1);
    e[hi] = q ? t : cf{0.f, 0.f};
    l128[hi] = cmul(l64[hi], l64[hi]);
    const cf l256 = cmul(l128[hi], l128[hi]);
    l512[hi] = cmul(l256, l256);
    l1024[hi] = cmul(l512[hi], l512[hi]);
  }
  if (rb > 0) {
    __nanosleep(AGG_DELAY);
    const uint4* src = g_agg + (rb - 1 - 4 * q) * 320 + rec;
    const uint64_t tg = tag_state({0.f, 0.f}, tag);
    uint64_t A[4][2];
    TLP(threadIdx.x == 0, 45);
    bool ok;
    do ok = ld_aggs(A, src, rb - 4 * q, tg);
    while (!__all_sync(~0u, ok));
    TLP(threadIdx.x == 0, 46);
#pragma unroll
    for (int hi = 0; hi < 2; hi++) {
      cf c = {0.f, 0.f};
#pragma unroll
      for (int u = 3; u >= 0; u--) {
        const cf a = {__uint_as_float((uint32_t)A[u][hi] & ~31u), __uint_as_float((uint32_t)(A[u][hi] >> 32) & ~31u)};
        c = u == 3 ? a : cfma(l128[hi], c, a);
      }
      cf t = shfl_dn4(c, 1);
      if (4 * q + 4 < rb) c = cfma(l512[hi], t, c);
      t = shfl_dn4(c, 2);
      if (rb > 8) c = cfma(l1024[hi], t, c);
      c = {__shfl_sync(~0u, c.r, 0, 4), __shfl_sync(~0u, c.i, 0, 4)};
      if (q & 1) c = cmul(c, cp.l32[hi]);
      if (q & 2) c = cmul(c, l64[hi]);
      e[hi].r += c.r;
      e[hi].i += c.i;
    }
  }
  __nv_bfloat16* dst = g_ht + (size_t)c0 * HP + rb * 128 + 8 * q;
  [[maybe_unused]] float dep = 0.f;
#pragma unroll
  for (int hi = 0; hi < 2; hi++) {
    cf s = e[hi];
    const uint32_t cr = pack_bf16(cp.coef[hi].r, cp.coef[hi].r), nci = pack_bf16(-cp.coef[hi].i, -cp.coef[hi].i), ncr = cr ^ 0x80008000u;
#pragma unroll
    for (int k = 0; k < 4; k++) {
      uint32_t pr[4], pi[4];
#pragma unroll
      for (int b = 0; b < 4; b++) {
        const int x = 4 * (4 * k + b) + 2 * hi;
        const cf s0 = cfma(cp.lam[hi], s, {ar[x], ai[x]});
        s = cfma(cp.lam[hi], s0, {ar[x + 1], ai[x + 1]});
        const uint32_t r2 = pack_bf16(s0.r, s.r), i2 = pack_bf16(s0.i, s.i);
        pr[b] = hfma2(cr, r2, hmul2(nci, i2));
        pi[b] = hfma2(ncr, i2, hmul2(nci, r2));
      }
      stg4(dst + (size_t)(8 * hi) * HP + 32 * k, pr[0], pr[1], pr[2], pr[3]);
      stg4(dst + (size_t)(640 + 8 * hi) * HP + 32 * k, pi[0], pi[1], pi[2], pi[3]);
    }
    dep = s.r;
    TLP(threadIdx.x == 0 && hi == 0, 47);
  }
}

template <bool SSM>
__device__ __forceinline__ void mainloop2(float (&acc)[80], uint32_t sb, int i0, int i1, int first, int wg, bool releaser, int& slot, uint32_t& par TL_ARG) {
  const uint32_t bars = sb + SM_MISC;
  const uint32_t dbase = (sb & 0x3FFFF) >> 4;
#pragma unroll 1
  for (int i = i0; i < i1; i++) {
    const uint32_t ds = dbase + slot * (SLOT2 >> 4);
    const uint32_t da = (ds + wg * 512) | (1u << 16), db = (ds + (XB >> 4)) | ((SSM ? 1u : 256u) << 16);
    mbar_wait(bars + B_FULL2 + slot * 8, par);
    wg_fence();
#pragma unroll
    for (int kk = 0; kk < 4; kk++) {
      if (SSM) wgmma_n160<1, 0>(acc, d64(da + kk * 128), d64(db + kk * 2), kk != 0 || i != first);
      else wgmma_n160<1, 1>(acc, d64(da + kk * 128), (uint64_t)(db + kk * 64) | (0x80000020ull << 32), kk != 0 || i != first);
    }
    wg_commit();
    wg_wait<1>();
    arrive_if(bars + B_EMPTY2 + (slot ? slot - 1 : NS2 - 1) * 8, releaser && i > 0);
    if (++slot == NS2) { slot = 0; par ^= 1; }
  }
}

template <int RANK>
__device__ __forceinline__ void phase2(const Params& p, uint32_t sb, int t0, int nt, bool five, int wg, int w,
                                       int lane, int tid TL_ARG) {
  const uint32_t bars = sb + SM_MISC;
  five = uni(five);
  wg = uni(wg);
  const int nk = five ? 27 - NFB : 20 + NFB, n1 = wg ? nk - LEAD : nk;
  float acc[80], accs[80];
  if (wg == (int)five) mbar_wait(bars + B_ORDER, wg ^ 1);
  TLP(w == 0 && lane == 0, 20 + wg);
  int slot = 0;
  uint32_t par = 0;
  mainloop2<false>(acc, sb, 0, five ? n1 : NFB, 0, wg, lane == 0, slot, par TL_PASS);
  if (!five) mainloop2<true>(accs, sb, NFB, n1, NFB, wg, lane == 0, slot, par TL_PASS);
  if (wg == 1) wg_wait<0>();
  arrive_if(wg == 0 ? bars + B_LEAD : bars + B_EMPTY2 + (slot ? slot - 1 : NS2 - 1) * 8, lane == 0);
  mbar_wait(bars + B_GREADY, 0);
  const int q = lane & 3;
  const bool odd = q & 1;
  const int col = nt * 160 + 80 * RANK + (odd ? 6 + 2 * q : 2 * q);
  uint32_t xv[2][5][2], dv[5][2];
#pragma unroll
  for (int v = 0; v < 5; v++) {
    asm volatile("ld.global.v2.b32 {%0,%1}, [%2];" : "=r"(xv[0][v][0]), "=r"(xv[0][v][1]) : "l"(p.px + (size_t)t0 * D_ + col + 16 * v) : "memory");
    asm volatile("ld.global.v2.b32 {%0,%1}, [%2];" : "=r"(xv[1][v][0]), "=r"(xv[1][v][1]) : "l"(p.px + (size_t)(t0 + 32) * D_ + col + 16 * v) : "memory");
    asm volatile("ld.global.v2.b32 {%0,%1}, [%2];" : "=r"(dv[v][0]), "=r"(dv[v][1]) : "l"(p.dskip + col + 16 * v) : "memory");
  }
  mbar_expect(bars + B_XCH + (wg * 4 + w) * 8, 2560);
  if (wg == 1) {
    mbar_wait(bars + B_LEAD, 0);
    if (five) mainloop2<false>(acc, sb, n1, nk, -1, wg, false, slot, par TL_PASS);
    else mainloop2<true>(accs, sb, n1, nk, -1, wg, false, slot, par TL_PASS);
  }
  const float g[2] = {lds_f(bars + M_G + (t0 & 127) * 4), lds_f(bars + M_G + (t0 & 127) * 4 + 128)};
  const float og[2] = {bf16r(1.f - g[0]), bf16r(1.f - g[1])};
  const uint32_t dst = mapa(sb + SM_XCH + (tid & ~3) * 16 + q * 8, RANK ^ 1);
  const uint32_t bar = mapa(bars + B_XCH + (wg * 4 + w) * 8, RANK ^ 1);
  mbar_wait_cluster(bars + B_XFREE, 0);
  wg_wait<0>();
  keep(acc);
  keep(accs);
  TLP(w == 0 && lane == 0, 22 + wg);
  float z[80];
#pragma unroll
  for (int h = 0; h < 2; h++) {
    const int x0 = 40 * (h ? RANK : 1 - RANK);
    if (five) {
#pragma unroll
      for (int i = 0; i < 40; i++) z[x0 + i] = acc[x0 + i] * og[(i >> 1) & 1];
    } else {
#pragma unroll
      for (int i = 0; i < 40; i++) z[x0 + i] = fmaf(og[(i >> 1) & 1], acc[x0 + i], g[(i >> 1) & 1] * accs[x0 + i]);
    }
    if (h == 0) {
#pragma unroll
      for (int v = 0; v < 5; v++) {
        const int x = x0 + 8 * v;
        asm volatile("st.async.weak.shared::cluster.mbarrier::complete_tx::bytes.v2.b32 [%0], {%1,%2}, [%3];"
                     ::"r"(dst + v * 4096), "r"(pack_bf16(z[x], z[x + 1])), "r"(pack_bf16(z[x + 2], z[x + 3])), "r"(bar) : "memory");
        asm volatile("st.async.weak.shared::cluster.mbarrier::complete_tx::bytes.v2.b32 [%0], {%1,%2}, [%3];"
                     ::"r"(dst + v * 4096 + 32), "r"(pack_bf16(z[x + 4], z[x + 5])), "r"(pack_bf16(z[x + 6], z[x + 7])), "r"(bar) : "memory");
      }
    }
  }
  float4 y[5][2];
#pragma unroll
  for (int v = 0; v < 5; v++)
#pragma unroll
    for (int hi = 0; hi < 2; hi++) {
      const int x = 40 * RANK + 8 * v + 2 * hi;
      const float s0 = __shfl_xor_sync(~0u, odd ? z[x] : z[x + 4], 1), s1 = __shfl_xor_sync(~0u, odd ? z[x + 1] : z[x + 5], 1);
      const uint32_t d0 = hmul2(xv[hi][v][0], dv[v][0]), d1 = hmul2(xv[hi][v][1], dv[v][1]);
      y[v][hi].x = fmaf(g[hi], __uint_as_float(d0 << 16), odd ? s0 : z[x]);
      y[v][hi].y = fmaf(g[hi], __uint_as_float(d0 & 0xffff0000u), odd ? s1 : z[x + 1]);
      y[v][hi].z = fmaf(g[hi], __uint_as_float(d1 << 16), odd ? z[x + 4] : s0);
      y[v][hi].w = fmaf(g[hi], __uint_as_float(d1 & 0xffff0000u), odd ? z[x + 5] : s1);
    }
  float* o = p.out + (size_t)t0 * D_ + col;
  const uint32_t src = sb + SM_XCH + (tid & ~3) * 16 + (odd ? 32 + (q - 1) * 8 : q * 8);
  mbar_wait_cluster(bars + B_XCH + (wg * 4 + w) * 8, 0);
  TLP(w == 0 && lane == 0, 24 + wg);
#pragma unroll
  for (int v = 0; v < 5; v++) {
    uint32_t u[4];
    asm volatile("ld.shared.v4.b32 {%0,%1,%2,%3}, [%4];" : "=r"(u[0]), "=r"(u[1]), "=r"(u[2]), "=r"(u[3]) : "r"(src + v * 4096));
#pragma unroll
    for (int hi = 0; hi < 2; hi++)
      *reinterpret_cast<float4*>(o + 32 * hi * D_ + 16 * v) =
          make_float4(y[v][hi].x + __uint_as_float(u[hi] << 16), y[v][hi].y + __uint_as_float(u[hi] & 0xffff0000u),
                      y[v][hi].z + __uint_as_float(u[2 + hi] << 16), y[v][hi].w + __uint_as_float(u[2 + hi] & 0xffff0000u));
  }
  TLP(w == 0 && lane == 0, 26 + wg);
}

__device__ __forceinline__ int tile_of(int j, int rnd) {
  return rnd == 0 ? j : rnd == 1 ? 8 + j : rnd == 4 ? 32 + (j >> 1) : 8 * rnd + j;
}

__device__ __forceinline__ int kblock_of(bool five, int i) {
  if (!five) return i < NFB ? 20 + i : i - NFB;
  const int c = i + NFB;
  return 20 + (c < 22 || (c > 22 && c < 26) ? c : 48 - c);
}

__device__ __forceinline__ uint32_t ld_epoch(uint32_t bars) {
  uint32_t tag;
  asm volatile("ld.shared.u32 %0, [%1];" : "=r"(tag) : "r"(bars + M_EPOCH) : "memory");
  return tag;
}

__device__ __forceinline__ void pf_next(const Params& p, int j, int half, int t, int kb) {
  if (t < 10) tma2_pf(half ? &p.bim : &p.bre, kb * 64, t * 64);
  else tma2_pf(half ? &p.wu : &p.wg, (t - 10) * 64, kb * 64);
}
__device__ __forceinline__ void cluster_arrive() { asm volatile("barrier.cluster.arrive.relaxed.aligned;" ::: "memory"); }
__device__ __forceinline__ void cluster_wait() { asm volatile("barrier.cluster.wait.aligned;" ::: "memory"); }
__device__ __forceinline__ void map_prefetch(const CUtensorMap* m) { asm volatile("prefetch.tensormap [%0];" ::"l"(m) : "memory"); }

__global__ void __cluster_dims__(2, 1, 1) __launch_bounds__(384, 1) fused_kernel(const __grid_constant__ Params p) {
  extern __shared__ __align__(1024) uint8_t smem_raw[];
  const uint32_t sb = (uint32_t)__cvta_generic_to_shared(smem_raw);
  const uint32_t bars = sb + SM_MISC;
  const int tid = threadIdx.x, warp = uni(tid >> 5), lane = tid & 31;
  const int rank = blockIdx.x & 1, pair = blockIdx.x >> 1;
  const int ps = pair < 4 ? 4 + pair : pair < 36 ? ((pair - 4) & 7) * 8 + ((pair - 4) >> 3)
               : pair < 64 ? (1 + (pair - 36) % 7) * 8 + 4 + (pair - 36) / 7 : pair;
  const bool spare = ps >= 64;
  const int j = ps & 7, sg = ps >> 3;
  const int rb = spare ? ((ps & 1) * 2 + rank) * 4 : (ps >> 3) * 2 + rank;
  const int rb2 = (ps >> 3) * 2 + (j >> 2);
  const bool five = !spare && rank == (j & 1);
  const int nt1 = five ? 5 : 4;

  if (warp == 8) {
    TLP(lane == 0, 28);
    if (lane == 0) {
#pragma unroll
      for (int i = 0; i < 14; i++) mbar_init(bars + B_XFULL + i * 8, 1);
      asm volatile("fence.mbarrier_init.release.cluster;" ::: "memory");
    }
    __syncwarp();
    TLP(lane == 0, 60);
    const CUtensorMap *m0 = spare ? &p.wg : &p.bre, *m1 = spare ? &p.wu : &p.bim;
    const uint32_t dx = spare ? SM_RING : 0, bx = spare ? B_FULL1 : B_XFULL;
#pragma unroll
    for (int kb = 0; kb < 4; kb++) {
      mbar_expect(bars + bx + kb * 8, XB);
      tma5(sb + dx + kb * XB, &p.x, bars + bx + kb * 8, kb * 64, 0, 0, 0, rb);
      mbar_expect(bars + B_FULL1 - bx + kb * 8, XB);
      tma2(sb + SM_RING - dx + kb * XB, m0, bars + B_FULL1 - bx + kb * 8, spare ? 26 * 64 : kb * 64, spare ? kb * 64 : j * 64);
      tma2(sb + SM_RING - dx + kb * XB + 8192, m1, bars + B_FULL1 - bx + kb * 8, spare ? 26 * 64 : kb * 64, spare ? kb * 64 : j * 64);
    }
    TLP(lane == 0, 61);
  } else if (tid == 288) {
#pragma unroll
    for (int i = 0; i < 4; i++) mbar_init(bars + B_EMPTY1 + i * 8, 8);
#pragma unroll
    for (int i = 0; i < NS2; i++) { mbar_init(bars + B_FULL2 + i * 8, 1); mbar_init(bars + B_EMPTY2 + i * 8, 8); }
    mbar_init(bars + B_XFREE, 8);
    mbar_init(bars + B_GREADY, 1);
    mbar_init(bars + B_ORDER, 4);
    asm volatile("fence.mbarrier_init.release.cluster;" ::: "memory");
  } else if (tid == 320) {
    if (sb & 1023) __trap();
#pragma unroll
    for (int i = 0; i < 8; i++) mbar_init(bars + B_XCH + i * 8, 1);
#pragma unroll
    for (int i = 0; i < 5; i++) mbar_init(bars + B_PUB + i * 8, 4);
    mbar_init(bars + B_EPOCH, 1);
    mbar_init(bars + B_DONE, 8);
    mbar_init(bars + B_PAR, 4);
    mbar_init(bars + B_LEAD, 4);
    asm volatile("st.shared.u32 [%0], %1;" ::"r"(bars + M_NREADY), "r"(0) : "memory");
    asm volatile("fence.mbarrier_init.release.cluster;" ::: "memory");
  }
  __syncthreads();
  cluster_arrive();

  if (warp >= 8) {
    asm volatile("setmaxnreg.dec.sync.aligned.u32 40;");
    if (warp == 8) {
      const int n1 = nt1 * 10;
      mbar_expect(bars + B_XFULL + 32, XB);
      if (!spare) {
        tma5(sb + 4 * XB, &p.x, bars + B_XFULL + 32, 4 * 64, 0, 0, 0, rb);
        if (sg < 6) tma2_pf(rank ? &p.bim : &p.bre, (4 + sg) * 64, j * 64);
        if (sg < 4) pf_next(p, j, rank, tile_of(j, 1), sg);
      } else {
        tma2(sb + 4 * XB, &p.wg, bars + B_XFULL + 32, 26 * 64, 4 * 64);
        tma2(sb + 4 * XB + 8192, &p.wu, bars + B_XFULL + 32, 26 * 64, 4 * 64);
      }
      cluster_wait();
      const uint32_t ring = sb + SM_RING;
      if (spare) {
#pragma unroll 1
        for (int it = 4, kb = 4, r = rb; it < 40; it++) {
          const uint32_t sl = it & 3, fb = bars + B_FULL1 + sl * 8;
          mbar_wait(bars + B_EMPTY1 + sl * 8, ((it >> 2) & 1) ^ 1);
          mbar_expect(fb, XB);
          tma5(ring + sl * XB, &p.x, fb, kb * 64, 0, 0, 0, r);
          if (it < 9) {
            const uint32_t xb = bars + B_XFULL + (it + 1) * 8, xd = sb + (it + 1) * XB;
            mbar_expect(xb, XB);
            tma2(xd, &p.wg, xb, 26 * 64, (it + 1) * 64);
            tma2(xd + 8192, &p.wu, xb, 26 * 64, (it + 1) * 64);
          }
          if (++kb == 10) { kb = 0; r++; }
        }
      } else {
        const CUtensorMap *mb = rank ? &p.bim : &p.bre, *mw = rank ? &p.wu : &p.wg;
        int it = 4;
#pragma unroll 1
        for (int rnd = 0; rnd < 4; rnd++) {
          const int t = tile_of(j, rnd), tn = tile_of(j, rnd + 1);
          const CUtensorMap *m = t < 10 ? mb : mw, *mn = tn < 10 ? mb : rnd < 3 ? mw : (j & 1) ? &p.wu : &p.wg;
          const int s0 = t < 10 ? 64 : 0, sn0 = tn < 10 ? 64 : 0, pf = rnd < 3 || five ? sg : 8;
          const int f0 = t < 10 ? 0 : (t - 10) * 64, f1 = t < 10 ? t * 64 : 0, g0 = tn < 10 ? 0 : (tn - 10) * 64, g1 = tn < 10 ? tn * 64 : 0;
#pragma unroll 1
          for (int kb = it - rnd * 10; kb < 10; kb++, it++) {
            const uint32_t sl = it & 3, fb = bars + B_FULL1 + sl * 8;
            mbar_wait(bars + B_EMPTY1 + sl * 8, ((it >> 2) & 1) ^ 1);
            mbar_expect(fb, XB);
            tma2_mc(ring + sl * XB + rank * 8192, m, fb, f0 + kb * s0, f1 + kb * (64 - s0));
            if (it < 9) {
              mbar_expect(bars + B_XFULL + (it + 1) * 8, XB);
              tma5(sb + (it + 1) * XB, &p.x, bars + B_XFULL + (it + 1) * 8, (it + 1) * 64, 0, 0, 0, rb);
            }
            if ((it & 7) == pf) tma2_pf(mn, g0 + kb * sn0, g1 + kb * (64 - sn0));
          }
        }
        if (five) {
          const int c0 = (22 + (j >> 1)) * 64;
#pragma unroll 1
          for (; it < 50; it++) {
            const uint32_t sl = it & 3, fb = bars + B_FULL1 + sl * 8;
            mbar_wait(bars + B_EMPTY1 + sl * 8, ((it >> 2) & 1) ^ 1);
            mbar_expect(fb, XB);
            tma2(ring + sl * XB, &p.wg, fb, c0, (it - 40) * 64);
            tma2(ring + sl * XB + 8192, &p.wu, fb, c0, (it - 40) * 64);
          }
        }
        TLP(lane == 0, 3);
        const int nk = five ? 27 - NFB : 20 + NFB, n0 = (j & 3) * 160;
        int slot = 0;
        uint32_t par = 1, nready = 0;
#pragma unroll 1
        for (int i = 0; i < nk; i++) {
          const int kbid = kblock_of(five, i);
          if (i >= NS2) {
            mbar_wait(bars + B_EMPTY2 + slot * 8, par);
          } else if (i >= 2) {
            const int r = n1 + 2 * i - 8;
            mbar_wait(bars + B_EMPTY1 + ((r - (i == 4)) & 3) * 8, ((r - (i == 4)) >> 2) & 1);
          }
          while (nready <= i) {
            asm volatile("ld.acquire.cta.shared.u32 %0, [%1];" : "=r"(nready) : "r"(bars + M_NREADY) : "memory");
            nready = uni(nready);
          }
          const uint32_t st = sb + slot * SLOT2, fb = bars + B_FULL2 + slot * 8;
          mbar_expect(fb, SLOT2);
          tma3(st, &p.ht, fb, 0, kbid * 64, rb2 * 2);
          if (kbid < 20) tma2(st + XB, &p.c[kbid >= 10], fb, (kbid >= 10 ? kbid - 10 : kbid) * 64, n0);
          else tma3(st + XB, &p.wd, fb, 0, (kbid - 20) * 64, (j & 3) * 5);
          TLP(lane == 0, 96 + i);
          TLP(i == 0 && lane == 0, 4);
          TLP(i == 4 && lane == 0, 5);
          if (++slot == NS2) { slot = 0; par ^= 1; }
        }
        TLP(lane == 0, 6);
      }
    } else {
      if (warp == 9) {
        uint32_t tag = 0;
        if (lane == 0) {
          tag = (uint32_t)(atomicAdd(&g_ticket, 1ull) / NCTA) + 1u;
          asm volatile("st.shared.u32 [%0], %1;" ::"r"(bars + M_EPOCH), "r"(tag) : "memory");
          mbar_arrive(bars + B_EPOCH);
        }
        tag = __shfl_sync(~0u, tag, 0);
        if (!spare) {
          if (lane < 6) map_prefetch(lane == 0 ? &p.wg : lane == 1 ? &p.wu : lane == 2 ? &p.ht : lane == 3 ? &p.wd : &p.c[lane & 1]);
          const int nk = five ? 27 - NFB : 20 + NFB, kbid = kblock_of(five, lane < nk ? lane : 0);
          const unsigned* flag = g_cnt + rb2 * 64 + (kbid < 10 ? kbid : kbid - 10);
          int nready = 0, spins = 0;
          mbar_wait_bounded(bars + B_PUB + (nt1 - 3) * 8, 0);
          while (nready < nk) {
            uint32_t v;
            asm volatile("ld.acquire.gpu.global.u32 %0, [%1];" : "=r"(v) : "l"(flag) : "memory");
            const int n = __ffs(__ballot_sync(~0u, v != tag || lane >= nk)) - 1;
            if (n > nready) {
              nready = n;
              asm volatile("fence.proxy.async.global;" ::: "memory");
              __syncwarp();
              TLP(lane == 0 && (n == 15 || n == 16 || n >= 20), n == 15 ? 35 : n == 16 ? 36 : 37);
              if (lane == 0) asm volatile("st.release.cta.shared.u32 [%0], %1;" ::"r"(bars + M_NREADY), "r"(n) : "memory");
            } else {
              __nanosleep(200);
            }
            if (++spins > (1 << 20)) __trap();
          }
        }
        mbar_wait_bounded(bars + B_DONE, 0);
      } else if (warp == 10) {
        const uint32_t tag = (mbar_wait_bounded(bars + B_EPOCH, 0), ld_epoch(bars));
#pragma unroll 1
        for (int rnd = 0; rnd < nt1; rnd++) {
          mbar_wait_bounded(bars + B_PUB + rnd * 8, 0);
          if (lane == 0) {
            unsigned* flag = spare ? g_cnt + (rb + rnd) * 64 + 36 : g_cnt + rb * 64 + tile_of(j, rnd);
            asm volatile("st.release.gpu.global.u32 [%0], %1;" ::"l"(flag), "r"(tag) : "memory");
          }
          TLP(lane == 0, 30 + rnd);
          __syncwarp();
        }
      } else if (!spare) {
        const int cta = rb * 8 + j;
        mbar_wait_bounded(bars + B_XFULL + 72, 0);
        const uint32_t tag = (mbar_wait_bounded(bars + B_EPOCH, 0), ld_epoch(bars));
#pragma unroll 1
        for (int i = lane; i < 100; i += 32) l2_prefetch((i < 50 ? p.pcre : p.pcim - 3200) + (size_t)cta * 3200 + i * 64);
        if (lane < 10) l2_prefetch(p.dskip + lane * 64);
        mbar_wait_bounded(bars + B_PUB + 8, 0);
#pragma unroll 1
        for (int i = lane; i < 135; i += 32) l2_prefetch(p.pwd + (size_t)cta * 5 * F_ + i * 64);
        const uint2* src = g_gate + rb2 * 128 + lane * 4;
        uint64_t v0, v1, v2, v3;
        int spins = 0;
        bool ok;
        do {
          __nanosleep(500);
          asm volatile("ld.relaxed.gpu.global.v2.b64 {%0,%1}, [%2];" : "=l"(v0), "=l"(v1) : "l"(src) : "memory");
          asm volatile("ld.relaxed.gpu.global.v2.b64 {%0,%1}, [%2];" : "=l"(v2), "=l"(v3) : "l"(src + 2) : "memory");
          ok = (uint32_t)(v0 >> 32) == tag && (uint32_t)(v1 >> 32) == tag && (uint32_t)(v2 >> 32) == tag && (uint32_t)(v3 >> 32) == tag;
          if (++spins > (1 << 20)) __trap();
        } while (!__all_sync(~0u, ok));
        asm volatile("st.shared.v4.b32 [%0], {%1,%2,%3,%4};" ::"r"(bars + M_G + lane * 16),
                     "r"((uint32_t)v0), "r"((uint32_t)v1), "r"((uint32_t)v2), "r"((uint32_t)v3) : "memory");
        __syncwarp();
        if (lane == 0) mbar_arrive(bars + B_GREADY);
        TLP(lane == 0, 7);
      }
      cluster_wait();
    }
  } else {
    asm volatile("setmaxnreg.inc.sync.aligned.u32 232;");
    const int wg = warp >> 2, w = warp & 3;
    if (!spare && wg == 1) {
      const uint4* xr = reinterpret_cast<const uint4*>(p.px + (size_t)(rb * 128 + j * 16 + w * 4 + (lane >> 3)) * D_) + (lane & 7);
      const uint4* gr = reinterpret_cast<const uint4*>(p.gw) + (lane & 7);
      uint4 xa[10], ga[10];
#pragma unroll
      for (int i = 0; i < 10; i++) { xa[i] = __ldg(xr + 8 * i); ga[i] = __ldg(gr + 8 * i); }
      const int c = (w < 2 || j >= 2 ? j * 64 : (8 + j) * 64) + (tid & 63);
      const float4 cp = chan_params(__bfloat162float(p.lre[c]), __bfloat162float(p.lim[c]), __bfloat162float(p.ldt[c]));
      asm volatile("st.shared.v4.f32 [%0], {%1,%2,%3,%4};" ::"r"(bars + M_PAR + (tid - 128) * 16), "f"(cp.x), "f"(cp.y), "f"(cp.z), "f"(cp.w) : "memory");
      const int t = rb * 128 + j * 16 + w * 4 + (lane >> 3);
      float z = 0.f;
#pragma unroll
      for (int i = 0; i < 10; i++) {
        const uint32_t pr[4] = {hmul2(xa[i].x, ga[i].x), hmul2(xa[i].y, ga[i].y), hmul2(xa[i].z, ga[i].z), hmul2(xa[i].w, ga[i].w)};
#pragma unroll
        for (int e = 0; e < 4; e++) z += __uint_as_float(pr[e] << 16) + __uint_as_float(pr[e] & 0xffff0000u);
      }
      z += __shfl_xor_sync(~0u, z, 1);
      z += __shfl_xor_sync(~0u, z, 2);
      z += __shfl_xor_sync(~0u, z, 4);
      const float g = bf16r(__fdividef(1.f, 1.f + __expf(-bf16r(z))));
      mbar_wait(bars + B_EPOCH, 0);
      if ((lane & 7) == 0)
        asm volatile("st.relaxed.gpu.global.b64 [%0], %1;" ::"l"(g_gate + t), "l"(((uint64_t)ld_epoch(bars) << 32) | __float_as_uint(g)) : "memory");
      __syncwarp();
      arrive_if(bars + B_PAR, lane == 0);
      TLP(tid == 128, 63);
    }
    cluster_wait();
    TLP(tid == 0, 62);
    const uint32_t rel_own = mapa(bars + B_EMPTY1, rank), rel_mc = mapa(bars + B_EMPTY1, spare ? rank : rank ^ (lane & 1));
    int rnd = wg;
    if (!spare && (wg == 0 || j < 2)) {
      float a0[64], a1[64];
      mainloop1<true>(a0, a1, sb, rnd, rel_mc, false, lane TL_PASS);
      TLP(w == 0 && lane == 0, 8 + 2 * rnd);
      mbar_wait(bars + B_PAR, 0);
      const int cl = 16 * w + (lane >> 2);
      const float4 p0 = lds_f4(bars + M_PAR + (64 * wg + cl) * 16), p1 = lds_f4(bars + M_PAR + (64 * wg + cl + 8) * 16);
      ChanPar cp = {{{p0.x, p0.y}, {p1.x, p1.y}}, {{p0.z, p0.w}, {p1.z, p1.w}}, {{p0.x, p0.y}, {p1.x, p1.y}}};
#pragma unroll
      for (int k = 0; k < 5; k++) { cp.l32[0] = cmul(cp.l32[0], cp.l32[0]); cp.l32[1] = cmul(cp.l32[1], cp.l32[1]); }
      ssm_epilogue(a0, a1, cp, rb, (8 * wg + j) * 64 + cl, lane, ld_epoch(bars), p.zero TL_PASS);
      __syncwarp();
      arrive_if(bars + B_PUB + rnd * 8, lane == 0);
      TLP(w == 0 && lane == 0, 9 + 2 * rnd);
      rnd += 2;
    }
    const int t0 = rb2 * 128 + 64 * (w & 1) + 8 * (2 * wg + (w >> 1)) + (lane >> 2);
#pragma unroll 1
    for (; rnd < nt1; rnd += 2) {
      float a0[64], a1[64];
      mainloop1<false>(a0, a1, sb, rnd, rnd < 4 ? rel_mc : rel_own, spare, lane TL_PASS);
      if (rnd + 2 >= nt1 && !spare) arrive_cluster_if(mapa(bars + B_XFREE, rank ^ 1), lane == 0);
      TLP(w == 0 && lane == 0, 8 + 2 * rnd);
      ffn_epilogue(a0, a1, spare ? rb + rnd : rb, (spare ? 26 : tile_of(j, rnd) - 10) * 64 + 16 * w + (lane >> 2), lane);
      __syncwarp();
      arrive_if(bars + B_PUB + rnd * 8, lane == 0);
      TLP(w == 0 && lane == 0, 9 + 2 * rnd);
    }
    if (!spare) {
      if (rank == 0) phase2<0>(p, sb, t0, j & 3, five, wg, w, lane, tid TL_PASS);
      else phase2<1>(p, sb, t0, j & 3, five, wg, w, lane, tid TL_PASS);
    }
    __syncwarp();
    arrive_if(bars + B_DONE, lane == 0);
  }
}

typedef CUresult (*EncodeFn)(CUtensorMap*, CUtensorMapDataType, cuuint32_t, void*, const cuuint64_t*, const cuuint64_t*, const cuuint32_t*,
                             const cuuint32_t*, CUtensorMapInterleave, CUtensorMapSwizzle, CUtensorMapL2promotion, CUtensorMapFloatOOBfill);

void make_map(EncodeFn enc, CUtensorMap* m, const void* base, int rank, const cuuint64_t* dims, const cuuint64_t* strides, const cuuint32_t* box,
              CUtensorMapSwizzle sw = CU_TENSOR_MAP_SWIZZLE_128B) {
  const cuuint32_t es[5] = {1, 1, 1, 1, 1};
  enc(m, CU_TENSOR_MAP_DATA_TYPE_BFLOAT16, rank, const_cast<void*>(base), dims, strides, box, es, CU_TENSOR_MAP_INTERLEAVE_NONE,
      sw, CU_TENSOR_MAP_L2_PROMOTION_L2_128B, CU_TENSOR_MAP_FLOAT_OOB_FILL_NONE);
}

}

extern "C" void kernel_launch(void* const* d_in, const int* in_sizes, int n_in, void* d_out, int out_size) {
  static EncodeFn enc = nullptr;
  static void* ht = nullptr;
  if (!enc) {
    void* fn = nullptr;
    cudaDriverEntryPointQueryResult qr;
    cudaGetDriverEntryPoint("cuTensorMapEncodeTiled", &fn, cudaEnableDefault, &qr);
    enc = (EncodeFn)fn;
    cudaGetSymbolAddress(&ht, g_ht);
    cudaFuncSetAttribute(fused_kernel, cudaFuncAttributeMaxDynamicSharedMemorySize, SMEM_BYTES);
  }
  typedef const __nv_bfloat16* bp;
  Params p;
  p.px = (bp)d_in[0]; p.lre = (bp)d_in[1]; p.lim = (bp)d_in[2]; p.pbre = (bp)d_in[3]; p.pbim = (bp)d_in[4];
  p.pcre = (bp)d_in[5]; p.pcim = (bp)d_in[6]; p.ldt = (bp)d_in[7]; p.dskip = (bp)d_in[8];
  p.pwg = (bp)d_in[10]; p.pwu = (bp)d_in[11]; p.pwd = (bp)d_in[12]; p.gw = (bp)d_in[13];
  p.out = (float*)d_out;
  {
    const cuuint64_t d[5] = {640, 2, 4, 16, 16}, s[4] = {1280, 32 * 1280, 2 * 1280, 128 * 1280};
    const cuuint32_t b[5] = {64, 2, 4, 16, 1};
    make_map(enc, &p.x, p.px, 5, d, s, b);
  }
  {
    const cuuint64_t d[2] = {640, 640}, s[1] = {1280};
    const cuuint32_t b[2] = {64, 64}, b160[2] = {64, 160};
    make_map(enc, &p.bre, p.pbre, 2, d, s, b);
    make_map(enc, &p.bim, p.pbim, 2, d, s, b);
    make_map(enc, &p.c[0], p.pcre, 2, d, s, b160);
    make_map(enc, &p.c[1], p.pcim, 2, d, s, b160);
  }
  {
    const cuuint64_t d[2] = {1728, 640}, s[1] = {3456};
    const cuuint32_t b[2] = {64, 64};
    make_map(enc, &p.wg, p.pwg, 2, d, s, b);
    make_map(enc, &p.wu, p.pwu, 2, d, s, b);
  }
  {
    const cuuint64_t d[3] = {64, 3008, 32}, s[2] = {HP * 2, 128};
    const cuuint32_t b[3] = {64, 64, 2};
    make_map(enc, &p.ht, ht, 3, d, s, b);
  }
  {
    const cuuint64_t d[3] = {32, 1728, 20}, s[2] = {1280, 64};
    const cuuint32_t b[3] = {32, 64, 5};
    make_map(enc, &p.wd, p.pwd, 3, d, s, b, CU_TENSOR_MAP_SWIZZLE_64B);
  }
  p.zero = 0;
  fused_kernel<<<NCTA, 384, SMEM_BYTES, cudaStreamPerThread>>>(p);
}
```

```cpp
#include <cuda_runtime.h>
#include <cuda.h>
#include <cuda_bf16.h>
#include <stdint.h>

namespace {

constexpr int L_ = 2048, D_ = 640, F_ = 1728;
#define HP 2048
constexpr int NCTA = 132;
constexpr int XB = 16384;
constexpr int SM_RING = 10 * XB;
constexpr int SM_MISC = 14 * XB;
constexpr int SLOT2 = 36864;
constexpr int NS2 = 5;
constexpr int SM_XCH = NS2 * SLOT2;
constexpr int SMEM_BYTES = SM_MISC + 3072;
#define LEAD 4
#define TLR 0
#define AGG_DELAY 400
#define NFB 12
#define PROMO_X CU_TENSOR_MAP_L2_PROMOTION_L2_128B
#define PROMO_W CU_TENSOR_MAP_L2_PROMOTION_L2_128B
#define GI 5
#define GW 0
constexpr int B_XFULL = 0;
constexpr int B_FULL1 = 80;
constexpr int B_EMPTY1 = 112;
constexpr int B_FULL2 = 144;
constexpr int B_EMPTY2 = 184;
constexpr int B_XCH = 224;
constexpr int B_PUB = 288;
constexpr int B_XFREE = 328;
constexpr int B_GREADY = 336;
constexpr int B_ORDER = 344;
constexpr int B_EPOCH = 352;
constexpr int B_DONE = 360;
constexpr int B_PAR = 368;
constexpr int B_LEAD = 376;
constexpr int M_EPOCH = 2944;
constexpr int M_NREADY = 2948;
constexpr int M_G = 384;
constexpr int M_PAR = 896;

struct Params {
  CUtensorMap x, bre, bim, wg, wu, ht, c[2], wd;
  const __nv_bfloat16 *px, *lre, *lim, *ldt, *dskip, *gw, *pbre, *pbim, *pcre, *pcim, *pwg, *pwu, *pwd;
  float* out;
};

__device__ __nv_bfloat16 g_ht[3008 * HP];
__device__ uint4 g_agg[16 * 320];
__device__ uint2 g_gate[2048];
__device__ unsigned g_cnt[16 * 64];
__device__ unsigned long long g_ticket;
#define TLP(c, i)

#define TL_ARG
#define TL_PASS
template <int TA, int TB>
__device__ __forceinline__ void wgmma_n128(float (&d)[64], uint64_t da, uint64_t db, int sc) {
  asm volatile("{\n.reg .pred p;\nsetp.ne.b32 p, %66, 0;\n"
    "wgmma.mma_async.sync.aligned.m64n128k16.f32.bf16.bf16 {%0,%1,%2,%3,%4,%5,%6,%7,%8,%9,%10,%11,%12,%13,%14,%15,%16,%17,%18,%19,%20,%21,%22,%23,%24,%25,%26,%27,%28,%29,%30,%31,%32,%33,%34,%35,%36,%37,%38,%39,%40,%41,%42,%43,%44,%45,%46,%47,%48,%49,%50,%51,%52,%53,%54,%55,%56,%57,%58,%59,%60,%61,%62,%63}, %64, %65, p, 1, 1, %67, %68;\n}\n"
    : "+f"(d[0]),"+f"(d[1]),"+f"(d[2]),"+f"(d[3]),"+f"(d[4]),"+f"(d[5]),"+f"(d[6]),"+f"(d[7]),"+f"(d[8]),"+f"(d[9]),"+f"(d[10]),"+f"(d[11]),"+f"(d[12]),"+f"(d[13]),"+f"(d[14]),"+f"(d[15]),"+f"(d[16]),"+f"(d[17]),"+f"(d[18]),"+f"(d[19]),"+f"(d[20]),"+f"(d[21]),"+f"(d[22]),"+f"(d[23]),"+f"(d[24]),"+f"(d[25]),"+f"(d[26]),"+f"(d[27]),"+f"(d[28]),"+f"(d[29]),"+f"(d[30]),"+f"(d[31]),"+f"(d[32]),"+f"(d[33]),"+f"(d[34]),"+f"(d[35]),"+f"(d[36]),"+f"(d[37]),"+f"(d[38]),"+f"(d[39]),"+f"(d[40]),"+f"(d[41]),"+f"(d[42]),"+f"(d[43]),"+f"(d[44]),"+f"(d[45]),"+f"(d[46]),"+f"(d[47]),"+f"(d[48]),"+f"(d[49]),"+f"(d[50]),"+f"(d[51]),"+f"(d[52]),"+f"(d[53]),"+f"(d[54]),"+f"(d[55]),"+f"(d[56]),"+f"(d[57]),"+f"(d[58]),"+f"(d[59]),"+f"(d[60]),"+f"(d[61]),"+f"(d[62]),"+f"(d[63])
    : "l"(da), "l"(db), "r"(sc), "n"(TA), "n"(TB));
}
template <int TA, int TB>
__device__ __forceinline__ void wgmma_n160(float (&d)[40], float (&e)[40], uint64_t da, uint64_t db, int sc) {
  asm volatile("{\n.reg .pred p;\nsetp.ne.b32 p, %82, 0;\n"
    "wgmma.mma_async.sync.aligned.m64n160k16.f32.bf16.bf16 {%0,%1,%2,%3,%4,%5,%6,%7,%8,%9,%10,%11,%12,%13,%14,%15,%16,%17,%18,%19,%20,%21,%22,%23,%24,%25,%26,%27,%28,%29,%30,%31,%32,%33,%34,%35,%36,%37,%38,%39,%40,%41,%42,%43,%44,%45,%46,%47,%48,%49,%50,%51,%52,%53,%54,%55,%56,%57,%58,%59,%60,%61,%62,%63,%64,%65,%66,%67,%68,%69,%70,%71,%72,%73,%74,%75,%76,%77,%78,%79}, %80, %81, p, 1, 1, %83, %84;\n}\n"
    : "+f"(d[0]),"+f"(d[1]),"+f"(d[2]),"+f"(d[3]),"+f"(d[4]),"+f"(d[5]),"+f"(d[6]),"+f"(d[7]),"+f"(d[8]),"+f"(d[9]),"+f"(d[10]),"+f"(d[11]),"+f"(d[12]),"+f"(d[13]),"+f"(d[14]),"+f"(d[15]),"+f"(d[16]),"+f"(d[17]),"+f"(d[18]),"+f"(d[19]),"+f"(d[20]),"+f"(d[21]),"+f"(d[22]),"+f"(d[23]),"+f"(d[24]),"+f"(d[25]),"+f"(d[26]),"+f"(d[27]),"+f"(d[28]),"+f"(d[29]),"+f"(d[30]),"+f"(d[31]),"+f"(d[32]),"+f"(d[33]),"+f"(d[34]),"+f"(d[35]),"+f"(d[36]),"+f"(d[37]),"+f"(d[38]),"+f"(d[39]),"+f"(e[0]),"+f"(e[1]),"+f"(e[2]),"+f"(e[3]),"+f"(e[4]),"+f"(e[5]),"+f"(e[6]),"+f"(e[7]),"+f"(e[8]),"+f"(e[9]),"+f"(e[10]),"+f"(e[11]),"+f"(e[12]),"+f"(e[13]),"+f"(e[14]),"+f"(e[15]),"+f"(e[16]),"+f"(e[17]),"+f"(e[18]),"+f"(e[19]),"+f"(e[20]),"+f"(e[21]),"+f"(e[22]),"+f"(e[23]),"+f"(e[24]),"+f"(e[25]),"+f"(e[26]),"+f"(e[27]),"+f"(e[28]),"+f"(e[29]),"+f"(e[30]),"+f"(e[31]),"+f"(e[32]),"+f"(e[33]),"+f"(e[34]),"+f"(e[35]),"+f"(e[36]),"+f"(e[37]),"+f"(e[38]),"+f"(e[39])
    : "l"(da), "l"(db), "r"(sc), "n"(TA), "n"(TB));
}
template <int TA, int TB>
__device__ __forceinline__ void wgmma_n80(float (&d)[40], uint64_t da, uint64_t db, int sc) {
  asm volatile("{\n.reg .pred p;\nsetp.ne.b32 p, %42, 0;\n"
    "wgmma.mma_async.sync.aligned.m64n80k16.f32.bf16.bf16 {%0,%1,%2,%3,%4,%5,%6,%7,%8,%9,%10,%11,%12,%13,%14,%15,%16,%17,%18,%19,%20,%21,%22,%23,%24,%25,%26,%27,%28,%29,%30,%31,%32,%33,%34,%35,%36,%37,%38,%39}, %40, %41, p, 1, 1, %43, %44;\n}\n"
    : "+f"(d[0]),"+f"(d[1]),"+f"(d[2]),"+f"(d[3]),"+f"(d[4]),"+f"(d[5]),"+f"(d[6]),"+f"(d[7]),"+f"(d[8]),"+f"(d[9]),"+f"(d[10]),"+f"(d[11]),"+f"(d[12]),"+f"(d[13]),"+f"(d[14]),"+f"(d[15]),"+f"(d[16]),"+f"(d[17]),"+f"(d[18]),"+f"(d[19]),"+f"(d[20]),"+f"(d[21]),"+f"(d[22]),"+f"(d[23]),"+f"(d[24]),"+f"(d[25]),"+f"(d[26]),"+f"(d[27]),"+f"(d[28]),"+f"(d[29]),"+f"(d[30]),"+f"(d[31]),"+f"(d[32]),"+f"(d[33]),"+f"(d[34]),"+f"(d[35]),"+f"(d[36]),"+f"(d[37]),"+f"(d[38]),"+f"(d[39])
    : "l"(da), "l"(db), "r"(sc), "n"(TA), "n"(TB));
}

#define ELECT "{\n.reg .pred e;\nelect.sync _|e, 0xffffffff;\n@e "
__device__ __forceinline__ void mbar_init(uint32_t b, int c) { asm volatile("mbarrier.init.shared::cta.b64 [%0], %1;" ::"r"(b), "r"(c)); }
__device__ __forceinline__ void mbar_expect(uint32_t b, int bytes) { asm volatile(ELECT "mbarrier.arrive.expect_tx.shared::cta.b64 _, [%0], %1;\n}" ::"r"(b), "r"(bytes) : "memory"); }
__device__ __forceinline__ void mbar_arrive(uint32_t b) { asm volatile("mbarrier.arrive.shared::cta.b64 _, [%0];" ::"r"(b) : "memory"); }
__device__ __forceinline__ void mbar_arrive2(uint32_t b) { asm volatile("mbarrier.arrive.shared::cta.b64 _, [%0], 2;" ::"r"(b) : "memory"); }
__device__ __forceinline__ void mbar_arrive_remote(uint32_t cluster_addr) { asm volatile("mbarrier.arrive.shared::cluster.b64 _, [%0];" ::"r"(cluster_addr) : "memory"); }
__device__ __forceinline__ uint32_t mapa(uint32_t a, uint32_t cta) { uint32_t r; asm("mapa.shared::cluster.u32 %0, %1, %2;" : "=r"(r) : "r"(a), "r"(cta)); return r; }
__device__ __forceinline__ void mbar_wait(uint32_t b, uint32_t parity) {
  asm volatile("{\n.reg .pred p;\nW: mbarrier.try_wait.parity.shared::cta.b64 p, [%0], %1;\n@!p bra W;\n}\n" ::"r"(b), "r"(parity) : "memory");
}
__device__ __forceinline__ void mbar_wait_long(uint32_t b, uint32_t parity) {
  asm volatile("{\n.reg .pred p;\nW: mbarrier.try_wait.parity.shared::cta.b64 p, [%0], %1, 2000;\n@!p bra W;\n}\n" ::"r"(b), "r"(parity) : "memory");
}
#define WAIT_ORDER mbar_wait
#define WAIT_PROD mbar_wait
__device__ __forceinline__ void mbar_wait_cluster(uint32_t b, uint32_t parity) {
  asm volatile("{\n.reg .pred p;\nW: mbarrier.try_wait.parity.acquire.cluster.shared::cta.b64 p, [%0], %1;\n@!p bra W;\n}\n" ::"r"(b), "r"(parity) : "memory");
}
__device__ __forceinline__ void mbar_spin_bounded(uint32_t b, uint32_t parity) {
  asm volatile(
      "{\n.reg .pred p;\n.reg .u32 c;\nmov.u32 c, 0;\n"
      "W: mbarrier.try_wait.parity.shared::cta.b64 p, [%0], %1;\n"
      "@p bra D;\n"
      "add.u32 c, c, 1;\nsetp.lt.u32 p, c, 0x1000000;\n@p bra W;\ntrap;\n"
      "D:\n}\n" ::"r"(b), "r"(parity) : "memory");
}
__device__ __forceinline__ void mbar_wait_bounded(uint32_t b, uint32_t parity) {
  asm volatile(
      "{\n.reg .pred p;\n.reg .u32 c;\nmov.u32 c, 0;\n"
      "W: mbarrier.try_wait.parity.shared::cta.b64 p, [%0], %1, 1000;\n"
      "@p bra D;\n"
      "add.u32 c, c, 1;\nsetp.lt.u32 p, c, 0x400000;\n@p bra W;\ntrap;\n"
      "D:\n}\n" ::"r"(b), "r"(parity) : "memory");
}
__device__ __forceinline__ void tma2(uint32_t dst, const CUtensorMap* m, uint32_t bar, int c0, int c1) {
  asm volatile(ELECT "cp.async.bulk.tensor.2d.shared::cluster.global.mbarrier::complete_tx::bytes [%0], [%1, {%3,%4}], [%2];\n}"
               ::"r"(dst), "l"(m), "r"(bar), "r"(c0), "r"(c1) : "memory");
}
__device__ __forceinline__ void tma2_mc(uint32_t dst, const CUtensorMap* m, uint32_t bar, int c0, int c1) {
  asm volatile(ELECT "cp.async.bulk.tensor.2d.shared::cluster.global.mbarrier::complete_tx::bytes.multicast::cluster [%0], [%1, {%3,%4}], [%2], %5;\n}"
               ::"r"(dst), "l"(m), "r"(bar), "r"(c0), "r"(c1), "h"((uint16_t)3) : "memory");
}
__device__ __forceinline__ void tma3(uint32_t dst, const CUtensorMap* m, uint32_t bar, int c0, int c1, int c2) {
  asm volatile(ELECT "cp.async.bulk.tensor.3d.shared::cluster.global.mbarrier::complete_tx::bytes [%0], [%1, {%3,%4,%5}], [%2];\n}"
               ::"r"(dst), "l"(m), "r"(bar), "r"(c0), "r"(c1), "r"(c2) : "memory");
}
__device__ __forceinline__ void tma5(uint32_t dst, const CUtensorMap* m, uint32_t bar, int c0, int c1, int c2, int c3, int c4) {
  asm volatile(ELECT "cp.async.bulk.tensor.5d.shared::cluster.global.mbarrier::complete_tx::bytes [%0], [%1, {%3,%4,%5,%6,%7}], [%2];\n}"
               ::"r"(dst), "l"(m), "r"(bar), "r"(c0), "r"(c1), "r"(c2), "r"(c3), "r"(c4) : "memory");
}
__device__ __forceinline__ void tma2_pf(const CUtensorMap* m, int c0, int c1) {
  asm volatile(ELECT "cp.async.bulk.prefetch.tensor.2d.L2.global [%0, {%1,%2}];\n}" ::"l"(m), "r"(c0), "r"(c1) : "memory");
}
__device__ __forceinline__ void tma5_pf(const CUtensorMap* m, int c0, int c4) {
  asm volatile(ELECT "cp.async.bulk.prefetch.tensor.5d.L2.global [%0, {%1,%2,%2,%2,%3}];\n}" ::"l"(m), "r"(c0), "r"(0), "r"(c4) : "memory");
}
__device__ __forceinline__ void l2_prefetch(const void* p) { asm volatile("prefetch.global.L2 [%0];" ::"l"(p)); }
__device__ __forceinline__ uint64_t desc(uint32_t addr, uint32_t lbo) {
  return (uint64_t)((addr & 0x3FFFF) >> 4) | ((uint64_t)(lbo >> 4) << 16) | (64ull << 32) | (1ull << 62);
}
__device__ __forceinline__ uint32_t dlo(uint32_t addr, uint32_t lbo) { return ((addr & 0x3FFFF) >> 4) | ((lbo >> 4) << 16); }
__device__ __forceinline__ uint64_t d64(uint32_t lo) { return (uint64_t)lo | (0x40000040ull << 32); }
__device__ __forceinline__ void arrive_if(uint32_t b, bool p) {
  asm volatile("{\n.reg .pred p;\nsetp.ne.b32 p, %1, 0;\n@p mbarrier.arrive.shared::cta.b64 _, [%0];\n}\n" ::"r"(b), "r"((int)p) : "memory");
}
__device__ __forceinline__ void arrive_cluster_if(uint32_t cluster_addr, bool p) {
  asm volatile("{\n.reg .pred p;\nsetp.ne.b32 p, %1, 0;\n@p mbarrier.arrive.shared::cluster.b64 _, [%0];\n}\n" ::"r"(cluster_addr), "r"((int)p) : "memory");
}
__device__ __forceinline__ int uni(int v) { return (int)__reduce_max_sync(~0u, (unsigned)v); }
__device__ __forceinline__ void wg_fence() { asm volatile("wgmma.fence.sync.aligned;" ::: "memory"); }
__device__ __forceinline__ void wg_commit() { asm volatile("wgmma.commit_group.sync.aligned;" ::: "memory"); }
template <int N> __device__ __forceinline__ void wg_wait() { asm volatile("wgmma.wait_group.sync.aligned %0;" ::"n"(N) : "memory"); }
template <int N> __device__ __forceinline__ void keep(float (&d)[N]) {
#pragma unroll
  for (int i = 0; i < N; i++) asm volatile("" : "+f"(d[i])::"memory");
}
__device__ __forceinline__ uint32_t pack_bf16(float lo, float hi) { uint32_t r; asm("cvt.rn.bf16x2.f32 %0, %1, %2;" : "=r"(r) : "f"(hi), "f"(lo)); return r; }
__device__ __forceinline__ float bf16r(float v) { return __bfloat162float(__float2bfloat16_rn(v)); }
__device__ __forceinline__ float lds_f(uint32_t a) { float v; asm volatile("ld.shared.f32 %0, [%1];" : "=f"(v) : "r"(a)); return v; }
__device__ __forceinline__ float4 lds_f4(uint32_t a) { float4 v; asm volatile("ld.shared.v4.f32 {%0,%1,%2,%3}, [%4];" : "=f"(v.x), "=f"(v.y), "=f"(v.z), "=f"(v.w) : "r"(a)); return v; }
__device__ __forceinline__ void stg4(void* p, uint32_t a, uint32_t b, uint32_t c, uint32_t d) {
  asm volatile("st.global.v4.b32 [%0], {%1,%2,%3,%4};" ::"l"(p), "r"(a), "r"(b), "r"(c), "r"(d) : "memory");
}
__device__ __forceinline__ uint32_t hmul2(uint32_t a, uint32_t b) { uint32_t r; asm("mul.rn.bf16x2 %0, %1, %2;" : "=r"(r) : "r"(a), "r"(b)); return r; }
__device__ __forceinline__ uint32_t hfma2(uint32_t a, uint32_t b, uint32_t c) { uint32_t r; asm("fma.rn.bf16x2 %0, %1, %2, %3;" : "=r"(r) : "r"(a), "r"(b), "r"(c)); return r; }
__device__ __forceinline__ uint4 lds_u4(uint32_t a) { uint4 v; asm volatile("ld.shared.v4.b32 {%0,%1,%2,%3}, [%4];" : "=r"(v.x), "=r"(v.y), "=r"(v.z), "=r"(v.w) : "r"(a)); return v; }
__device__ __forceinline__ float fsel(bool c, float a, float b) {
  float r;
  asm("{\n.reg .pred p;\nsetp.ne.b32 p, %3, 0;\nselp.f32 %0, %1, %2, p;\n}\n" : "=f"(r) : "f"(a), "f"(b), "r"((int)c));
  return r;
}
struct cf { float r, i; };
__device__ __forceinline__ cf cmul(cf a, cf b) { return {a.r * b.r - a.i * b.i, a.r * b.i + a.i * b.r}; }
__device__ __forceinline__ cf cfma(cf a, cf b, cf c) { return {fmaf(-a.i, b.i, fmaf(a.r, b.r, c.r)), fmaf(a.i, b.r, fmaf(a.r, b.i, c.i))}; }

template <bool SSM>
__device__ __forceinline__ void mainloop1(float (&a0)[64], float (&a1)[64], uint32_t sb, int rnd, uint32_t rel, bool swap, int lane TL_ARG) {
  const uint32_t bars = sb + SM_MISC;
  rnd = uni(rnd);
  if (!SSM) swap = uni(swap);
  if (rnd > 0) WAIT_ORDER(bars + B_ORDER, (rnd - 1) & 1);
  const bool releaser = lane < 2;
  const uint32_t dbase = (sb & 0x3FFFF) >> 4;
  int it = rnd * 10;
#pragma unroll 1
  for (int kb = 0; kb < 10; kb++, it++) {
    const uint32_t slot = it & 3;
    uint32_t dw = dbase + (SM_RING >> 4) + slot * (XB >> 4), dx = dbase + kb * (XB >> 4);
    if (!SSM && swap) { const uint32_t t = dw; dw = dx; dx = t; }
    dx |= 1u << 16;
    dw |= 1u << 16;
    if (rnd < 2) mbar_wait(bars + B_XFULL + kb * 8, 0);
    mbar_wait(bars + B_FULL1 + slot * 8, (it >> 2) & 1);
    wg_fence();
#pragma unroll
    for (int kk = 0; kk < 4; kk++) {
      const int sc = (kb | kk) != 0;
      if (SSM) {
        wgmma_n128<0, 0>(a0, d64(dw + kk * 2), d64(dx + kk * 2), sc);
        wgmma_n128<0, 0>(a1, d64(dw + 512 + kk * 2), d64(dx + kk * 2), sc);
      } else {
        wgmma_n128<1, 0>(a0, d64(dw + kk * 128), d64(dx + kk * 2), sc);
        wgmma_n128<1, 0>(a1, d64(dw + 512 + kk * 128), d64(dx + kk * 2), sc);
      }
    }
    wg_commit();
    wg_wait<1>();
    arrive_cluster_if(rel + ((it - 1) & 3) * 8, releaser && kb > 0);
  }
  arrive_if(bars + B_ORDER, lane == 0);
  wg_wait<0>();
  keep(a0);
  keep(a1);
  arrive_cluster_if(rel + ((it - 1) & 3) * 8, releaser);
}

__device__ __forceinline__ void ffn_epilogue(float (&ag)[64], float (&au)[64], uint32_t og, int rb, int u0, int lane) {
  __nv_bfloat16* dst = g_ht + (size_t)(1280 + u0) * HP + rb * 128 + 8 * (lane & 3);
#pragma unroll
  for (int k = 0; k < 4; k++) {
    const uint4 o4 = lds_u4(og + 16 * k);
    const uint32_t o[4] = {o4.x, o4.y, o4.z, o4.w};
#pragma unroll
    for (int hi = 0; hi < 2; hi++) {
      uint32_t pk[4];
#pragma unroll
      for (int b = 0; b < 4; b++) {
        float v[2];
#pragma unroll
        for (int e = 0; e < 2; e++) {
          const int x = 4 * (4 * k + b) + 2 * hi + e;
          const float hz = 0.5f * ag[x], pu = hz * au[x];
          float th;
          asm("tanh.approx.f32 %0, %1;" : "=f"(th) : "f"(hz));
          v[e] = fmaf(pu, th, pu);
        }
        pk[b] = hmul2(pack_bf16(v[0], v[1]), o[b]);
      }
      stg4(dst + (size_t)(8 * hi) * HP + 32 * k, pk[0], pk[1], pk[2], pk[3]);
    }
  }
}

struct ChanPar { cf lam[2], coef[2], l32[2]; };
__device__ __forceinline__ float4 chan_params(float lr, float li, float ldt) {
  const float dt = bf16r(expf(ldt));
  const float e = expf(dt * lr);
  float s, co;
  sincosf(dt * li, &s, &co);
  const float nr = e * co - 1.f, ni = e * s;
  const bool big = fabsf(lr) >= fabsf(li);
  const float a = big ? lr : li, b = big ? li : lr, t = b / a, inv = 2.f / (a + b * t);
  return make_float4(e * co, ni, (big ? nr + ni * t : nr * t + ni) * inv, (big ? ni - nr * t : ni * t - nr) * inv);
}

__device__ __forceinline__ cf shfl_up4(cf v, int d) { return {__shfl_up_sync(~0u, v.r, d, 4), __shfl_up_sync(~0u, v.i, d, 4)}; }
__device__ __forceinline__ cf shfl_dn4(cf v, int d) { return {__shfl_down_sync(~0u, v.r, d, 4), __shfl_down_sync(~0u, v.i, d, 4)}; }

__device__ __forceinline__ uint64_t tag_state(cf v, uint32_t tag) {
  return ((uint64_t)((__float_as_uint(v.i) & ~31u) | ((tag >> 5) & 31u)) << 32) | ((__float_as_uint(v.r) & ~31u) | (tag & 31u));
}
__device__ __forceinline__ bool ld_aggs(uint64_t (&v)[4][2], const uint4* src, int n, uint64_t tg) {
  uint64_t bad = 0;
#pragma unroll
  for (int u = 0; u < 4; u++) {
    v[u][0] = v[u][1] = tg;
    asm volatile("{\n.reg .pred p;\nsetp.gt.s32 p, %3, 0;\n@p ld.relaxed.gpu.global.v2.b64 {%0,%1}, [%2];\n}\n"
                 : "+l"(v[u][0]), "+l"(v[u][1]) : "l"(src - u * 320), "r"(n - u) : "memory");
  }
#pragma unroll
  for (int u = 0; u < 4; u++) bad |= (v[u][0] ^ tg) | (v[u][1] ^ tg);
  return (bad & 0x1f0000001full) == 0;
}

template <class V>
__device__ __forceinline__ void scan_store(cf s, cf lam, cf coef, uint32_t gs, __nv_bfloat16* dst, V v) {
  const uint32_t cr = pack_bf16(coef.r, coef.r), nci = pack_bf16(-coef.i, -coef.i), ncr = cr ^ 0x80008000u;
#pragma unroll
  for (int k = 0; k < 4; k++) {
    const uint4 g4 = lds_u4(gs + 16 * k);
    const uint32_t g[4] = {g4.x, g4.y, g4.z, g4.w};
    uint32_t pr[4], pi[4];
#pragma unroll
    for (int b = 0; b < 4; b++) {
      const cf s0 = cfma(lam, s, v(4 * k + b, 0));
      s = cfma(lam, s0, v(4 * k + b, 1));
      const uint32_t r2 = pack_bf16(s0.r, s.r), i2 = pack_bf16(s0.i, s.i);
      pr[b] = hmul2(hfma2(cr, r2, hmul2(nci, i2)), g[b]);
      pi[b] = hmul2(hfma2(ncr, i2, hmul2(nci, r2)), g[b]);
    }
    stg4(dst + 32 * k, pr[0], pr[1], pr[2], pr[3]);
    stg4(dst + (size_t)640 * HP + 32 * k, pi[0], pi[1], pi[2], pi[3]);
  }
}

__device__ __forceinline__ void ssm_epilogue(float (&ar)[64], float (&ai)[64], const ChanPar& cp, uint32_t bars, int rb, int c0, int lane, uint32_t tag,
                                             uint32_t (&pend)[32], cf& e1 TL_ARG) {
  const int q = lane & 3;
  cf h[2], e[2], l64[2];
#pragma unroll
  for (int hi = 0; hi < 2; hi++) h[hi] = {ar[2 * hi], ai[2 * hi]};
#pragma unroll
  for (int i = 1; i < 32; i++)
#pragma unroll
    for (int hi = 0; hi < 2; hi++) {
      const int x = 4 * (i >> 1) + 2 * hi + (i & 1);
      h[hi] = cfma(cp.lam[hi], h[hi], {ar[x], ai[x]});
    }
#pragma unroll
  for (int hi = 0; hi < 2; hi++) {
    l64[hi] = cmul(cp.l32[hi], cp.l32[hi]);
    cf t = shfl_up4(h[hi], 1);
    if (q >= 1) h[hi] = cfma(cp.l32[hi], t, h[hi]);
    t = shfl_up4(h[hi], 2);
    if (q >= 2) h[hi] = cfma(l64[hi], t, h[hi]);
  }
  const int rec = (c0 >> 4) * 8 + (c0 & 7);
  if (q == 3 && rb < 15)
    asm volatile("st.relaxed.gpu.global.v2.b64 [%0], {%1,%2};" ::"l"(g_agg + rb * 320 + rec), "l"(tag_state(h[0], tag)), "l"(tag_state(h[1], tag)) : "memory");
  TLP(threadIdx.x == 0, 49);
#pragma unroll
  for (int x = 0; x < 16; x++) {
    pend[2 * x] = pack_bf16(ar[4 * x + 2], ar[4 * x + 3]);
    pend[2 * x + 1] = pack_bf16(ai[4 * x + 2], ai[4 * x + 3]);
  }
  cf l128[2], l512[2], l1024[2];
#pragma unroll
  for (int hi = 0; hi < 2; hi++) {
    const cf t = shfl_up4(h[hi], 1);
    e[hi] = q ? t : cf{0.f, 0.f};
    l128[hi] = cmul(l64[hi], l64[hi]);
    const cf l256 = cmul(l128[hi], l128[hi]);
    l512[hi] = cmul(l256, l256);
    l1024[hi] = cmul(l512[hi], l512[hi]);
  }
  if (rb > 0) {
    if (AGG_DELAY) __nanosleep(AGG_DELAY);
    const uint4* src = g_agg + (rb - 1 - 4 * q) * 320 + rec;
    const uint64_t tg = tag_state({0.f, 0.f}, tag);
    uint64_t A[4][2];
    TLP(threadIdx.x == 0, 45);
    bool ok;
    do ok = ld_aggs(A, src, rb - 4 * q, tg);
    while (!__all_sync(~0u, ok));
    TLP(threadIdx.x == 0, 46);
#pragma unroll
    for (int hi = 0; hi < 2; hi++) {
      cf c = {0.f, 0.f};
#pragma unroll
      for (int u = 3; u >= 0; u--) {
        const cf a = {__uint_as_float((uint32_t)A[u][hi] & ~31u), __uint_as_float((uint32_t)(A[u][hi] >> 32) & ~31u)};
        c = u == 3 ? a : cfma(l128[hi], c, a);
      }
      cf t = shfl_dn4(c, 1);
      if (4 * q + 4 < rb) c = cfma(l512[hi], t, c);
      t = shfl_dn4(c, 2);
      if (rb > 8) c = cfma(l1024[hi], t, c);
      c = {__shfl_sync(~0u, c.r, 0, 4), __shfl_sync(~0u, c.i, 0, 4)};
      if (q & 1) c = cmul(c, cp.l32[hi]);
      if (q & 2) c = cmul(c, l64[hi]);
      e[hi].r += c.r;
      e[hi].i += c.i;
    }
  }
  mbar_wait(bars + B_GREADY, 0);
  scan_store(e[0], cp.lam[0], cp.coef[0], bars + M_G + 64 * q, g_ht + (size_t)c0 * HP + rb * 128 + 8 * q,
             [&](int x, int e2) { return cf{ar[4 * x + e2], ai[4 * x + e2]}; });
  e1 = e[1];
}

__device__ __forceinline__ int tile_of(int j, bool five, int rnd) {
  return rnd == 0 ? j : rnd == 1 ? (j >= 4 ? 8 + j : (five ? 8 : 10) + (j >> 1)) : rnd == 4 ? 32 + (j >> 1) : 8 * rnd + j;
}

__device__ __forceinline__ int kblock_of(bool five, int i) {
  const int c = five ? i + NFB : i, s = five ? c - 27 + 20 - LEAD : c - NFB;
  if (c >= (five ? 27 : NFB)) return (s >> 1) + 10 * (s & 1);
  return c < 14 ? 20 + c : 34 + (int)((0x98ba3210c7654ull >> (4 * (c - 14))) & 15);
}
__device__ __forceinline__ int nk_of(bool five) { return five ? 27 - NFB + LEAD : 20 - LEAD + NFB; }

template <bool SSM>
__device__ __forceinline__ void mainloop2(float (&lo)[40], float (&hi)[40], uint32_t sb, int i0, int i1, int wg, bool releaser, int& slot,
                                          uint32_t& par TL_ARG) {
  const uint32_t bars = sb + SM_MISC;
  const uint32_t dbase = (sb & 0x3FFFF) >> 4;
#pragma unroll 1
  for (int i = i0; i < i1; i++) {
    const uint32_t ds = dbase + slot * (SLOT2 >> 4);
    const uint32_t da = (ds + wg * 512) | (1u << 16), db = (ds + (XB >> 4)) | ((SSM ? 1u : 256u) << 16);
    mbar_wait(bars + B_FULL2 + slot * 8, par);
    wg_fence();
#pragma unroll
    for (int kk = 0; kk < 4; kk++) {
      if (SSM) wgmma_n160<1, 0>(lo, hi, d64(da + kk * 128), d64(db + kk * 2), 1);
      else wgmma_n160<1, 1>(lo, hi, d64(da + kk * 128), (uint64_t)(db + kk * 64) | (0x80000020ull << 32), kk != 0 || i != 0);
    }
    wg_commit();
    wg_wait<1>();
    arrive_if(bars + B_EMPTY2 + (slot ? slot - 1 : NS2 - 1) * 8, releaser && i > 0);
    TLP(threadIdx.x == 0, 64 + i);
    if (++slot == NS2) { slot = 0; par ^= 1; }
  }
}

__device__ __forceinline__ void half_blocks(float (&acc)[40], uint32_t sb, int half, bool wait, int slot, uint32_t par) {
  const uint32_t dbase = (sb & 0x3FFFF) >> 4;
  wg_fence();
#pragma unroll 1
  for (int i = 0; i < LEAD; i++) {
    const uint32_t ds = dbase + slot * (SLOT2 >> 4);
    const uint32_t da = (ds + 512) | (1u << 16), db = (ds + (XB >> 4) + half * 640) | (1u << 16);
    if (wait) mbar_wait(sb + SM_MISC + B_FULL2 + slot * 8, par);
#pragma unroll
    for (int kk = 0; kk < 4; kk++) wgmma_n80<1, 0>(acc, d64(da + kk * 128), d64(db + kk * 2), 1);
    if (++slot == NS2) { slot = 0; par ^= 1; }
  }
  wg_commit();
}

template <int RANK>
__device__ __forceinline__ void phase2(const Params& p, uint32_t sb, int t0, int nt, bool five, int wg, int w, int lane, int tid TL_ARG) {
  const uint32_t bars = sb + SM_MISC;
  five = uni(five);
  wg = uni(wg);
  const int nk = nk_of(five);
  float a0[40], a1[40];
  if (wg == (int)five) WAIT_ORDER(bars + B_ORDER, wg ^ 1);
  TLP(w == 0 && lane == 0, 20 + wg);
  int slot = 0;
  uint32_t par = 0;
  mainloop2<false>(a0, a1, sb, 0, five ? nk - LEAD : NFB, wg, lane == 0, slot, par TL_PASS);
  mainloop2<true>(a0, a1, sb, five ? nk : NFB, nk - LEAD, wg, lane == 0, slot, par TL_PASS);
  const int q = lane & 3;
  const bool odd = q & 1;
  const int col = nt * 160 + 80 * RANK + (odd ? 6 + 2 * q : 2 * q);
  uint32_t xv[2][5][2], dv[5][2];
  float g[2];
#pragma unroll
  for (int v = 0; v < 5; v++) {
    asm volatile("ld.global.v2.b32 {%0,%1}, [%2];" : "=r"(xv[0][v][0]), "=r"(xv[0][v][1]) : "l"(p.px + (size_t)t0 * D_ + col + 16 * v) : "memory");
    asm volatile("ld.global.v2.b32 {%0,%1}, [%2];" : "=r"(xv[1][v][0]), "=r"(xv[1][v][1]) : "l"(p.px + (size_t)(t0 + 32) * D_ + col + 16 * v) : "memory");
    asm volatile("ld.global.v2.b32 {%0,%1}, [%2];" : "=r"(dv[v][0]), "=r"(dv[v][1]) : "l"(p.dskip + col + 16 * v) : "memory");
  }
  asm volatile("ld.relaxed.gpu.global.f32 %0, [%1];" : "=f"(g[0]) : "l"(g_gate + t0) : "memory");
  asm volatile("ld.relaxed.gpu.global.f32 %0, [%1];" : "=f"(g[1]) : "l"(g_gate + t0 + 32) : "memory");
  mbar_expect(bars + B_XCH + (wg * 4 + w) * 8, 2560);
  const uint32_t dst = mapa(sb + SM_XCH + (tid & ~3) * 16 + q * 8, RANK ^ 1);
  const uint32_t bar = mapa(bars + B_XCH + (wg * 4 + w) * 8, RANK ^ 1);
  mbar_wait(bars + B_XFREE, 0);
  auto finish = [&](float (&sendv)[40], float (&keepv)[40]) {
    keep(sendv);
    TLP(w == 0 && lane == 0, 36 + wg);
#pragma unroll
    for (int v = 0; v < 10; v++)
      asm volatile("st.async.weak.shared::cluster.mbarrier::complete_tx::bytes.v2.b32 [%0], {%1,%2}, [%3];"
                   ::"r"(dst + (v >> 1) * 4096 + (v & 1) * 32), "r"(pack_bf16(sendv[4 * v], sendv[4 * v + 1])),
                   "r"(pack_bf16(sendv[4 * v + 2], sendv[4 * v + 3])), "r"(bar) : "memory");
    wg_wait<0>();
    keep(keepv);
    TLP(w == 0 && lane == 0, 22 + wg);
    float4 y[5][2];
#pragma unroll
    for (int v = 0; v < 5; v++)
#pragma unroll
      for (int hi = 0; hi < 2; hi++) {
        const float z0 = keepv[8 * v + 2 * hi], z1 = keepv[8 * v + 2 * hi + 1], z4 = keepv[8 * v + 2 * hi + 4], z5 = keepv[8 * v + 2 * hi + 5];
        float s0, s1;
        s0 = __shfl_xor_sync(~0u, fsel(odd, z0, z4), 1);
        s1 = __shfl_xor_sync(~0u, fsel(odd, z1, z5), 1);
        const uint32_t d0 = hmul2(xv[hi][v][0], dv[v][0]), d1 = hmul2(xv[hi][v][1], dv[v][1]);
        y[v][hi].x = fmaf(g[hi], __uint_as_float(d0 << 16), fsel(odd, s0, z0));
        y[v][hi].y = fmaf(g[hi], __uint_as_float(d0 & 0xffff0000u), fsel(odd, s1, z1));
        y[v][hi].z = fmaf(g[hi], __uint_as_float(d1 << 16), fsel(odd, z4, s0));
        y[v][hi].w = fmaf(g[hi], __uint_as_float(d1 & 0xffff0000u), fsel(odd, z5, s1));
      }
    float* o = p.out + (size_t)t0 * D_ + col;
    const uint32_t src = sb + SM_XCH + (tid & ~3) * 16 + (odd ? 32 + (q - 1) * 8 : q * 8);
    mbar_wait_cluster(bars + B_XCH + (wg * 4 + w) * 8, 0);
    TLP(w == 0 && lane == 0, 24 + wg);
#pragma unroll
    for (int v = 0; v < 5; v++) {
      const uint4 u4 = lds_u4(src + v * 4096);
      const uint32_t u[4] = {u4.x, u4.y, u4.z, u4.w};
#pragma unroll
      for (int hi = 0; hi < 2; hi++)
        *reinterpret_cast<float4*>(o + 32 * hi * D_ + 16 * v) =
            make_float4(y[v][hi].x + __uint_as_float(u[hi] << 16), y[v][hi].y + __uint_as_float(u[hi] & 0xffff0000u),
                        y[v][hi].z + __uint_as_float(u[2 + hi] << 16), y[v][hi].w + __uint_as_float(u[2 + hi] & 0xffff0000u));
    }
    TLP(w == 0 && lane == 0, 26 + wg);
  };
  if (wg == 0) {
    mainloop2<true>(a0, a1, sb, nk - LEAD, nk, 0, false, slot, par TL_PASS);
    arrive_if(bars + B_LEAD, lane == 0);
    wg_wait<0>();
    finish(RANK ? a0 : a1, RANK ? a1 : a0);
  } else {
    wg_wait<0>();
    keep(a0);
    keep(a1);
    float bs[40], bk[40];
#pragma unroll
    for (int i = 0; i < 40; i++) { bs[i] = RANK ? a0[i] : a1[i]; bk[i] = RANK ? a1[i] : a0[i]; }
    keep(bs);
    keep(bk);
    WAIT_ORDER(bars + B_LEAD, 0);
    half_blocks(bs, sb, 1 - RANK, true, slot, par);
    half_blocks(bk, sb, RANK, false, slot, par);
    wg_wait<1>();
    finish(bs, bk);
  }
}

__device__ __forceinline__ uint32_t ld_epoch(uint32_t bars) {
  uint32_t tag;
  asm volatile("ld.shared.u32 %0, [%1];" : "=r"(tag) : "r"(bars + M_EPOCH) : "memory");
  return tag;
}

__device__ __forceinline__ void pf_next(const Params& p, int j, int half, int t, int kb) {
  if (t < 10) tma2_pf(half ? &p.bim : &p.bre, kb * 64, t * 64);
  else tma2_pf(half ? &p.wu : &p.wg, (t - 10) * 64, kb * 64);
}
__device__ __forceinline__ void cluster_arrive() { asm volatile("barrier.cluster.arrive.relaxed.aligned;" ::: "memory"); }
__device__ __forceinline__ void cluster_wait() { asm volatile("barrier.cluster.wait.aligned;" ::: "memory"); }
__device__ __forceinline__ void map_prefetch(const CUtensorMap* m) { asm volatile("prefetch.tensormap [%0];" ::"l"(m) : "memory"); }

__global__ void __cluster_dims__(2, 1, 1) __launch_bounds__(384, 1) fused_kernel(const __grid_constant__ Params p) {
  extern __shared__ __align__(1024) uint8_t smem_raw[];
  const uint32_t sb = (uint32_t)__cvta_generic_to_shared(smem_raw);
  const uint32_t bars = sb + SM_MISC;
  uint32_t clk0;
  asm volatile("mov.u32 %0, %%clock;" : "=r"(clk0));
  const int tid = threadIdx.x, warp = uni(tid >> 5), lane = tid & 31;
  const int rank = blockIdx.x & 1, pair = blockIdx.x >> 1;
  const int ps = pair < 4 ? 4 + pair : pair < 36 ? ((pair - 4) & 7) * 8 + ((pair - 4) >> 3)
               : pair < 64 ? (1 + (pair - 36) % 7) * 8 + 4 + (pair - 36) / 7 : pair;
  const bool spare = ps >= 64;
  const int j = ps & 7, sg = ps >> 3;
  const int rb = spare ? ((ps & 1) * 2 + rank) * 4 : (ps >> 3) * 2 + rank;
  const int rb2 = (ps >> 3) * 2 + (j >> 2);
  const bool five = !spare && rank == (j & 1);
  const int nt1 = five ? 5 : 4;

  if (warp >= 8) {
    asm volatile("setmaxnreg.dec.sync.aligned.u32 40;");
    if (warp == 8) {
      TLP(lane == 0, 28);
      if (lane == 0) {
  #pragma unroll
        for (int i = 0; i < 14; i++) mbar_init(bars + B_XFULL + i * 8, 1);
        asm volatile("fence.mbarrier_init.release.cluster;" ::: "memory");
      }
      __syncwarp();
      asm volatile("bar.arrive 1, 384;" ::: "memory");
      TLP(lane == 0, 60);
      const CUtensorMap *m0 = spare ? &p.wg : &p.bre, *m1 = spare ? &p.wu : &p.bim;
      const uint32_t dx = spare ? SM_RING : 0, bx = spare ? B_FULL1 : B_XFULL;
  #pragma unroll
      for (int kb = 0; kb < 4; kb++) {
        mbar_expect(bars + bx + kb * 8, XB);
        tma5(sb + dx + kb * XB, &p.x, bars + bx + kb * 8, kb * 64, 0, 0, 0, rb);
        mbar_expect(bars + B_FULL1 - bx + kb * 8, XB);
        tma2(sb + SM_RING - dx + kb * XB, m0, bars + B_FULL1 - bx + kb * 8, spare ? 26 * 64 : kb * 64, spare ? kb * 64 : j * 64);
        tma2(sb + SM_RING - dx + kb * XB + 8192, m1, bars + B_FULL1 - bx + kb * 8, spare ? 26 * 64 : kb * 64, spare ? kb * 64 : j * 64);
      }
      TLP(lane == 0, 61);
      cluster_arrive();
      const int n1 = nt1 * 10;
      mbar_expect(bars + B_XFULL + 32, XB);
      if (!spare) {
        tma5(sb + 4 * XB, &p.x, bars + B_XFULL + 32, 4 * 64, 0, 0, 0, rb);
        if (sg < 6) tma2_pf(rank ? &p.bim : &p.bre, (4 + sg) * 64, j * 64);
        if (sg < 4) pf_next(p, j, j < 4 ? j & 1 : rank, tile_of(j, five, 1), sg);
      } else {
        tma2(sb + 4 * XB, &p.wg, bars + B_XFULL + 32, 26 * 64, 4 * 64);
        tma2(sb + 4 * XB + 8192, &p.wu, bars + B_XFULL + 32, 26 * 64, 4 * 64);
      }
      cluster_wait();
      const uint32_t ring = sb + SM_RING;
      if (spare) {
#pragma unroll 1
        for (int it = 4, kb = 4, r = rb; it < 40; it++) {
          const uint32_t sl = it & 3, fb = bars + B_FULL1 + sl * 8;
          WAIT_PROD(bars + B_EMPTY1 + sl * 8, ((it >> 2) & 1) ^ 1);
          mbar_expect(fb, XB);
          tma5(ring + sl * XB, &p.x, fb, kb * 64, 0, 0, 0, r);
          if (it < 9) {
            const uint32_t xb = bars + B_XFULL + (it + 1) * 8, xd = sb + (it + 1) * XB;
            mbar_expect(xb, XB);
            tma2(xd, &p.wg, xb, 26 * 64, (it + 1) * 64);
            tma2(xd + 8192, &p.wu, xb, 26 * 64, (it + 1) * 64);
          }
          if (++kb == 10) { kb = 0; r++; }
        }
      } else {
        int it = 4;
#pragma unroll 1
        for (int rnd = 0; rnd < 4; rnd++) {
          const int t = tile_of(j, five, rnd), tn = tile_of(j, five, rnd + 1);
          const bool own = rnd == 1 && j < 4, ownn = rnd == 3 || (rnd == 0 && j < 4);
          const CUtensorMap *m = (t < 10 ? &p.bre : &p.wg) + (own ? 0 : rank), *mn = (tn < 10 ? &p.bre : &p.wg) + (ownn ? j & 1 : rank);
          const int s0 = t < 10 ? 64 : 0, sn0 = tn < 10 ? 64 : 0, pf = rnd < 3 || five ? sg : 8;
          const int f0 = t < 10 ? 0 : (t - 10) * 64, f1 = t < 10 ? t * 64 : 0, g0 = tn < 10 ? 0 : (tn - 10) * 64, g1 = tn < 10 ? tn * 64 : 0;
#pragma unroll 1
          for (int kb = it - rnd * 10; kb < 10; kb++, it++) {
            const uint32_t sl = it & 3, fb = bars + B_FULL1 + sl * 8;
            WAIT_PROD(bars + B_EMPTY1 + sl * 8, ((it >> 2) & 1) ^ 1);
            mbar_expect(fb, XB);
            if (own) {
              tma2(ring + sl * XB, m, fb, f0 + kb * s0, f1 + kb * (64 - s0));
              tma2(ring + sl * XB + 8192, m + 1, fb, f0 + kb * s0, f1 + kb * (64 - s0));
            } else {
              tma2_mc(ring + sl * XB + rank * 8192, m, fb, f0 + kb * s0, f1 + kb * (64 - s0));
            }
            if (it < 9) {
              mbar_expect(bars + B_XFULL + (it + 1) * 8, XB);
              tma5(sb + (it + 1) * XB, &p.x, bars + B_XFULL + (it + 1) * 8, (it + 1) * 64, 0, 0, 0, rb);
            }
            if ((it & 7) == pf) tma2_pf(mn, g0 + kb * sn0, g1 + kb * (64 - sn0));
          }
        }
        if (five) {
          const int c0 = (22 + (j >> 1)) * 64;
#pragma unroll 1
          for (; it < 50; it++) {
            const uint32_t sl = it & 3, fb = bars + B_FULL1 + sl * 8;
            WAIT_PROD(bars + B_EMPTY1 + sl * 8, ((it >> 2) & 1) ^ 1);
            mbar_expect(fb, XB);
            tma2(ring + sl * XB, &p.wg, fb, c0, (it - 40) * 64);
            tma2(ring + sl * XB + 8192, &p.wu, fb, c0, (it - 40) * 64);
          }
        }
        TLP(lane == 0, 3);
        const int nk = nk_of(five), n0 = (j & 3) * 160;
        int slot = 0;
        uint32_t par = 1, nready = 0;
#pragma unroll 1
        for (int i = 0; i < nk; i++) {
          const int kbid = kblock_of(five, i);
          if (i >= NS2) {
            WAIT_PROD(bars + B_EMPTY2 + slot * 8, par);
          } else if (i >= 2) {
            const int r = n1 + 2 * i - 8;
            WAIT_PROD(bars + B_EMPTY1 + ((r - (i == 4)) & 3) * 8, ((r - (i == 4)) >> 2) & 1);
          }
          while (nready <= i) {
            asm volatile("ld.acquire.cta.shared.u32 %0, [%1];" : "=r"(nready) : "r"(bars + M_NREADY) : "memory");
            nready = uni(nready);
          }
          const uint32_t st = sb + slot * SLOT2, fb = bars + B_FULL2 + slot * 8;
          mbar_expect(fb, SLOT2);
          tma3(st, &p.ht, fb, 0, kbid * 64, rb2 * 2);
          if (kbid < 20) tma2(st + XB, &p.c[kbid >= 10], fb, (kbid >= 10 ? kbid - 10 : kbid) * 64, n0);
          else tma3(st + XB, &p.wd, fb, 0, (kbid - 20) * 64, (j & 3) * 5);
          TLP(lane == 0, 96 + i);
          TLP(i == 0 && lane == 0, 4);
          TLP(i == 4 && lane == 0, 5);
          if (++slot == NS2) { slot = 0; par ^= 1; }
        }
        TLP(lane == 0, 6);
      }
    } else {
      if (tid == 288) {
#pragma unroll
    for (int i = 0; i < 4; i++) mbar_init(bars + B_EMPTY1 + i * 8, 8);
#pragma unroll
    for (int i = 0; i < NS2; i++) { mbar_init(bars + B_FULL2 + i * 8, 1); mbar_init(bars + B_EMPTY2 + i * 8, 8); }
    mbar_init(bars + B_XFREE, 8);
    mbar_init(bars + B_GREADY, 1);
    mbar_init(bars + B_ORDER, 4);
    asm volatile("fence.mbarrier_init.release.cluster;" ::: "memory");
  } else if (tid == 320) {
    if (sb & 1023) __trap();
#pragma unroll
    for (int i = 0; i < 8; i++) mbar_init(bars + B_XCH + i * 8, 1);
#pragma unroll
    for (int i = 0; i < 5; i++) mbar_init(bars + B_PUB + i * 8, 4);
    mbar_init(bars + B_EPOCH, 1);
    mbar_init(bars + B_DONE, 8);
    mbar_init(bars + B_PAR, 4);
    mbar_init(bars + B_LEAD, 4);
    asm volatile("st.shared.u32 [%0], %1;" ::"r"(bars + M_NREADY), "r"(0) : "memory");
    asm volatile("fence.mbarrier_init.release.cluster;" ::: "memory");
  }
      __syncwarp();
      asm volatile("bar.sync 1, 384;" ::: "memory");
      cluster_arrive();
      if (warp == 9) {
        uint32_t tag = 0;
        if (lane == 0) {
          tag = (uint32_t)(atomicAdd(&g_ticket, 1ull) / NCTA) + 1u;
          asm volatile("st.shared.u32 [%0], %1;" ::"r"(bars + M_EPOCH), "r"(tag) : "memory");
          mbar_arrive(bars + B_EPOCH);
        }
        tag = __shfl_sync(~0u, tag, 0);
        if (!spare) {
          if (lane < 6) map_prefetch(lane == 0 ? &p.wg : lane == 1 ? &p.wu : lane == 2 ? &p.ht : lane == 3 ? &p.wd : &p.c[lane & 1]);
          const int nk = nk_of(five), kbid = kblock_of(five, lane < nk ? lane : 0);
          const unsigned* flag = g_cnt + rb2 * 64 + (kbid < 10 ? kbid : kbid - 10);
          int nready = 0, spins = 0;
          mbar_wait_bounded(bars + B_PUB, 0);
          while (nready < nk) {
            uint32_t v;
            asm volatile("ld.acquire.gpu.global.u32 %0, [%1];" : "=r"(v) : "l"(flag) : "memory");
            const int n = __ffs(__ballot_sync(~0u, v != tag || lane >= nk)) - 1;
            if (n > nready) {
              nready = n;
              asm volatile("fence.proxy.async.global;" ::: "memory");
              __syncwarp();
              if (lane == 0) asm volatile("st.release.cta.shared.u32 [%0], %1;" ::"r"(bars + M_NREADY), "r"(n) : "memory");
            } else {
              __nanosleep(200);
            }
            if (++spins > (1 << 20)) __trap();
          }
        }
        mbar_wait_bounded(bars + B_DONE, 0);
      } else {
        const uint32_t tag = (mbar_wait_bounded(bars + B_EPOCH, 0), ld_epoch(bars));
        if (warp == 11) {
          const int cta = rb * 8 + j;
          mbar_wait_bounded(bars + B_XFULL + 64, 0);
#pragma unroll 1
          for (int r = 0; r < (spare ? 4 : 1); r++) {
            const uint2* src = g_gate + (rb + r) * 128 + lane * 4;
            uint64_t v0, v1, v2, v3;
            int spins = 0;
            bool ok;
            do {
              __nanosleep(300);
              asm volatile("ld.relaxed.gpu.global.v2.b64 {%0,%1}, [%2];" : "=l"(v0), "=l"(v1) : "l"(src) : "memory");
              asm volatile("ld.relaxed.gpu.global.v2.b64 {%0,%1}, [%2];" : "=l"(v2), "=l"(v3) : "l"(src + 2) : "memory");
              ok = (uint32_t)(v0 >> 32) == tag && (uint32_t)(v1 >> 32) == tag && (uint32_t)(v2 >> 32) == tag && (uint32_t)(v3 >> 32) == tag;
              if (++spins > (1 << 20)) __trap();
            } while (!__all_sync(~0u, ok));
            const float g0 = __uint_as_float((uint32_t)v0), g1 = __uint_as_float((uint32_t)v1), g2 = __uint_as_float((uint32_t)v2), g3 = __uint_as_float((uint32_t)v3);
            const uint32_t dst = bars + (spare ? M_PAR + 512 * r : M_G) + lane * 8;
            asm volatile("st.shared.v2.b32 [%0], {%1,%2};" ::"r"(dst), "r"(pack_bf16(g0, g1)), "r"(pack_bf16(g2, g3)) : "memory");
            asm volatile("st.shared.v2.b32 [%0], {%1,%2};" ::"r"(dst + 256), "r"(pack_bf16(1.f - g0, 1.f - g1)), "r"(pack_bf16(1.f - g2, 1.f - g3)) : "memory");
          }
          __syncwarp();
          if (lane == 0) mbar_arrive(bars + B_GREADY);
          TLP(lane == 0, 7);
          if (!spare) {
#pragma unroll 1
            for (int i = lane; i < 135; i += 32) l2_prefetch(p.pwd + (size_t)cta * 5 * F_ + i * 64);
            if (lane < 10) l2_prefetch(p.dskip + lane * 64);
            __nanosleep(2000);
#pragma unroll 1
            for (int i = lane; i < 100; i += 32) l2_prefetch((i < 50 ? p.pcre : p.pcim - 3200) + (size_t)cta * 3200 + i * 64);
          }
        }
#pragma unroll 1
        for (int rnd = warp - 10; rnd < nt1; rnd += 2) {
          mbar_wait_bounded(bars + B_PUB + rnd * 8, 0);
          if (lane == 0) {
            unsigned* flag = spare ? g_cnt + (rb + rnd) * 64 + 36 : g_cnt + rb * 64 + tile_of(j, five, rnd);
            asm volatile("st.release.gpu.global.u32 [%0], %1;" ::"l"(flag), "r"(tag) : "memory");
          }
          TLP(lane == 0, 30 + rnd);
          __syncwarp();
        }
      }
      cluster_wait();
    }
  } else {
    TLP(tid == 0, 41);
    asm volatile("setmaxnreg.inc.sync.aligned.u32 232;");
    TLP(tid == 0, 42);
    asm volatile("bar.sync 1, 384;" ::: "memory");
    TLP(tid == 0, 40);
    cluster_arrive();
    const int wg = warp >> 2, w = warp & 3;
    if (!spare && wg == 1) {
      const int c = (w < 2 || j >= 4 ? j : 8 + (j >> 1)) * 64 + (tid & 63);
      const float4 cp = chan_params(__bfloat162float(p.lre[c]), __bfloat162float(p.lim[c]), __bfloat162float(p.ldt[c]));
      asm volatile("st.shared.v4.f32 [%0], {%1,%2,%3,%4};" ::"r"(bars + M_PAR + (tid - 128) * 16), "f"(cp.x), "f"(cp.y), "f"(cp.z), "f"(cp.w) : "memory");
      mbar_wait(bars + B_XFULL + GW * 8, 0);
      const uint4* xr = reinterpret_cast<const uint4*>(p.px + (size_t)(rb * 128 + j * 16 + w * 4 + (lane >> 3)) * D_) + (lane & 7);
      const uint4* gr = reinterpret_cast<const uint4*>(p.gw) + (lane & 7);
      uint4 xa[10], ga[10];
#pragma unroll
      for (int i = 0; i < 10; i++) { xa[i] = xr[8 * i]; ga[i] = gr[8 * i]; }
      const int t = rb * 128 + j * 16 + w * 4 + (lane >> 3);
      float z = 0.f;
#pragma unroll
      for (int i = 0; i < 10; i++) {
        const uint32_t pr[4] = {hmul2(xa[i].x, ga[i].x), hmul2(xa[i].y, ga[i].y), hmul2(xa[i].z, ga[i].z), hmul2(xa[i].w, ga[i].w)};
#pragma unroll
        for (int e = 0; e < 4; e++) z += __uint_as_float(pr[e] << 16) + __uint_as_float(pr[e] & 0xffff0000u);
      }
      z += __shfl_xor_sync(~0u, z, 1);
      z += __shfl_xor_sync(~0u, z, 2);
      z += __shfl_xor_sync(~0u, z, 4);
      const float g = bf16r(__fdividef(1.f, 1.f + __expf(-bf16r(z))));
      mbar_wait(bars + B_EPOCH, 0);
      if ((lane & 7) == 0)
        asm volatile("st.relaxed.gpu.global.b64 [%0], %1;" ::"l"(g_gate + t), "l"(((uint64_t)ld_epoch(bars) << 32) | __float_as_uint(g)) : "memory");
      __syncwarp();
      arrive_if(bars + B_PAR, lane == 0);
      TLP(tid == 128, 63);
    }
    cluster_wait();
    TLP(tid == 0, 62);
    const uint32_t rel_own = mapa(bars + B_EMPTY1, rank), rel_mc = mapa(bars + B_EMPTY1, spare ? rank : rank ^ (lane & 1));
    int rnd = wg;
    bool pending = !spare && (wg == 0 || (j < 4 && five));
    const int cb = wg ? 8 + (j >> 1) : j;
    const int cl = 16 * w + (lane >> 2);
    uint32_t pend[32];
    cf e1;
    if (pending) {
      float a0[64], a1[64];
      mainloop1<true>(a0, a1, sb, rnd, rel_mc, false, lane TL_PASS);
      TLP(w == 0 && lane == 0, 8 + 2 * rnd);
      mbar_wait(bars + B_PAR, 0);
      const float4 p0 = lds_f4(bars + M_PAR + (64 * wg + cl) * 16), p1 = lds_f4(bars + M_PAR + (64 * wg + cl + 8) * 16);
      ChanPar cp = {{{p0.x, p0.y}, {p1.x, p1.y}}, {{p0.z, p0.w}, {p1.z, p1.w}}, {{p0.x, p0.y}, {p1.x, p1.y}}};
#pragma unroll
      for (int k = 0; k < 5; k++) { cp.l32[0] = cmul(cp.l32[0], cp.l32[0]); cp.l32[1] = cmul(cp.l32[1], cp.l32[1]); }
      ssm_epilogue(a0, a1, cp, bars, rb, cb * 64 + cl, lane, ld_epoch(bars), pend, e1 TL_PASS);
      TLP(w == 0 && lane == 0, 9 + 2 * rnd);
      rnd += 2;
    }
    const int t0 = rb2 * 128 + 64 * (w & 1) + 8 * (2 * wg + (w >> 1)) + (lane >> 2);
#pragma unroll 1
    for (; rnd < nt1; rnd += 2) {
      float a0[64], a1[64];
      mainloop1<false>(a0, a1, sb, rnd, rnd < 4 ? rel_mc : rel_own, spare, lane TL_PASS);
      if (rnd + 2 >= nt1 && !spare) arrive_cluster_if(mapa(bars + B_XFREE, rank ^ 1), lane == 0);
      TLP(w == 0 && lane == 0, 8 + 2 * rnd);
      if (pending) {
        const float4 p1 = lds_f4(bars + M_PAR + (64 * wg + cl + 8) * 16);
        scan_store(e1, {p1.x, p1.y}, {p1.z, p1.w}, bars + M_G + 64 * (lane & 3), g_ht + (size_t)(cb * 64 + cl + 8) * HP + rb * 128 + 8 * (lane & 3),
                   [&](int x, int e2) {
                     return e2 ? cf{__uint_as_float(pend[2 * x] & 0xffff0000u), __uint_as_float(pend[2 * x + 1] & 0xffff0000u)}
                               : cf{__uint_as_float(pend[2 * x] << 16), __uint_as_float(pend[2 * x + 1] << 16)};
                   });
        __syncwarp();
        arrive_if(bars + B_PUB + wg * 8, lane == 0);
        TLP(tid == 0, 47);
        pending = false;
      }
      mbar_wait(bars + B_GREADY, 0);
      ffn_epilogue(a0, a1, bars + (spare ? M_PAR + 512 * rnd : M_G) + 256 + 64 * (lane & 3), spare ? rb + rnd : rb, (spare ? 26 : tile_of(j, five, rnd) - 10) * 64 + cl, lane);
      __syncwarp();
      arrive_if(bars + B_PUB + rnd * 8, lane == 0);
      TLP(w == 0 && lane == 0, 9 + 2 * rnd);
    }
    if (!spare) {
      if (rank == 0) phase2<0>(p, sb, t0, j & 3, five, wg, w, lane, tid TL_PASS);
      else phase2<1>(p, sb, t0, j & 3, five, wg, w, lane, tid TL_PASS);
    }
    __syncwarp();
    arrive_if(bars + B_DONE, lane == 0);
  }
}

typedef CUresult (*EncodeFn)(CUtensorMap*, CUtensorMapDataType, cuuint32_t, void*, const cuuint64_t*, const cuuint64_t*, const cuuint32_t*,
                             const cuuint32_t*, CUtensorMapInterleave, CUtensorMapSwizzle, CUtensorMapL2promotion, CUtensorMapFloatOOBfill);

void make_map(EncodeFn enc, CUtensorMap* m, const void* base, int rank, const cuuint64_t* dims, const cuuint64_t* strides, const cuuint32_t* box,
              CUtensorMapSwizzle sw = CU_TENSOR_MAP_SWIZZLE_128B, CUtensorMapL2promotion pr = CU_TENSOR_MAP_L2_PROMOTION_L2_128B) {
  const cuuint32_t es[5] = {1, 1, 1, 1, 1};
  enc(m, CU_TENSOR_MAP_DATA_TYPE_BFLOAT16, rank, const_cast<void*>(base), dims, strides, box, es, CU_TENSOR_MAP_INTERLEAVE_NONE,
      sw, pr, CU_TENSOR_MAP_FLOAT_OOB_FILL_NONE);
}

}

extern "C" void kernel_launch(void* const* d_in, const int* in_sizes, int n_in, void* d_out, int out_size) {
  static EncodeFn enc = nullptr;
  static void* ht = nullptr;
  if (!enc) {
    void* fn = nullptr;
    cudaDriverEntryPointQueryResult qr;
    cudaGetDriverEntryPoint("cuTensorMapEncodeTiled", &fn, cudaEnableDefault, &qr);
    enc = (EncodeFn)fn;
    cudaGetSymbolAddress(&ht, g_ht);
    cudaFuncSetAttribute(fused_kernel, cudaFuncAttributeMaxDynamicSharedMemorySize, SMEM_BYTES);
  }
  typedef const __nv_bfloat16* bp;
  Params p;
  p.px = (bp)d_in[0]; p.lre = (bp)d_in[1]; p.lim = (bp)d_in[2]; p.pbre = (bp)d_in[3]; p.pbim = (bp)d_in[4];
  p.pcre = (bp)d_in[5]; p.pcim = (bp)d_in[6]; p.ldt = (bp)d_in[7]; p.dskip = (bp)d_in[8];
  p.pwg = (bp)d_in[10]; p.pwu = (bp)d_in[11]; p.pwd = (bp)d_in[12]; p.gw = (bp)d_in[13];
  p.out = (float*)d_out;
  {
    const cuuint64_t d[5] = {640, 2, 4, 16, 16}, s[4] = {1280, 32 * 1280, 2 * 1280, 128 * 1280};
    const cuuint32_t b[5] = {64, 2, 4, 16, 1};
    make_map(enc, &p.x, p.px, 5, d, s, b, CU_TENSOR_MAP_SWIZZLE_128B, PROMO_X);
  }
  {
    const cuuint64_t d[2] = {640, 640}, s[1] = {1280};
    const cuuint32_t b[2] = {64, 64}, b160[2] = {64, 160};
    make_map(enc, &p.bre, p.pbre, 2, d, s, b, CU_TENSOR_MAP_SWIZZLE_128B, PROMO_X);
    make_map(enc, &p.bim, p.pbim, 2, d, s, b, CU_TENSOR_MAP_SWIZZLE_128B, PROMO_X);
    make_map(enc, &p.c[0], p.pcre, 2, d, s, b160);
    make_map(enc, &p.c[1], p.pcim, 2, d, s, b160);
  }
  {
    const cuuint64_t d[2] = {1728, 640}, s[1] = {3456};
    const cuuint32_t b[2] = {64, 64};
    make_map(enc, &p.wg, p.pwg, 2, d, s, b, CU_TENSOR_MAP_SWIZZLE_128B, PROMO_W);
    make_map(enc, &p.wu, p.pwu, 2, d, s, b, CU_TENSOR_MAP_SWIZZLE_128B, PROMO_W);
  }
  {
    const cuuint64_t d[3] = {64, 3008, 32}, s[2] = {HP * 2, 128};
    const cuuint32_t b[3] = {64, 64, 2};
    make_map(enc, &p.ht, ht, 3, d, s, b);
  }
  {
    const cuuint64_t d[3] = {32, 1728, 20}, s[2] = {1280, 64};
    const cuuint32_t b[3] = {32, 64, 5};
    make_map(enc, &p.wd, p.pwd, 3, d, s, b, CU_TENSOR_MAP_SWIZZLE_64B);
  }
  fused_kernel<<<NCTA, 384, SMEM_BYTES, cudaStreamPerThread>>>(p);
}
```

```cpp
#include <cuda_runtime.h>
#include <cuda.h>
#include <cuda_bf16.h>
#include <stdint.h>

namespace {

constexpr int L_ = 2048, D_ = 640, F_ = 1728;
constexpr int NCTA = 132;
constexpr int XB = 16384;
constexpr int SM_RING = 10 * XB;
constexpr int SM_MISC = 14 * XB;
constexpr int SLOT2 = 40960;
constexpr int NS2 = 5;
constexpr int SM_XCH = NS2 * SLOT2;
constexpr int SMEM_BYTES = SM_MISC + 3072;
constexpr int LEAD = 4;
constexpr int NFB = 8;
constexpr uint32_t AGG_DELAY = 950;
constexpr uint32_t REL = 500;
constexpr int B_XFULL = 0;
constexpr int B_FULL1 = 80;
constexpr int B_EMPTY1 = 112;
constexpr int B_FULL2 = 144;
constexpr int B_EMPTY2 = 184;
constexpr int B_XCH = 224;
constexpr int B_PUB = 288;
constexpr int B_XFREE = 328;
constexpr int B_GREADY = 336;
constexpr int B_ORDER = 344;
constexpr int B_EPOCH = 352;
constexpr int B_DONE = 360;
constexpr int B_PAR = 368;
constexpr int B_LEAD = 376;
constexpr int B_XS = 2952;
constexpr int M_EPOCH = 2944;
constexpr int M_NREADY = 2948;
constexpr int M_G = 384;
constexpr int M_PAR = 896;

struct Params {
  CUtensorMap x, bre, bim, wg, wu, ht, c128[2], c32[2], wd, xs, wdh[4];
  const __nv_bfloat16 *px, *lre, *lim, *ldt, *dskip, *gw, *pbre, *pbim, *pcre, *pcim, *pwg, *pwu, *pwd;
  float* out;
};

__device__ __nv_bfloat16 g_ht[3008 * L_];
__device__ uint4 g_agg[16 * 320];
__device__ uint2 g_gate[2048];
__device__ unsigned g_cnt[16 * 64];
__device__ unsigned long long g_ticket;

template <int TA, int TB>
__device__ __forceinline__ void wgmma_n128(float (&d)[64], uint64_t da, uint64_t db, int sc) {
  asm volatile("{\n.reg .pred p;\nsetp.ne.b32 p, %66, 0;\n"
    "wgmma.mma_async.sync.aligned.m64n128k16.f32.bf16.bf16 {%0,%1,%2,%3,%4,%5,%6,%7,%8,%9,%10,%11,%12,%13,%14,%15,%16,%17,%18,%19,%20,%21,%22,%23,%24,%25,%26,%27,%28,%29,%30,%31,%32,%33,%34,%35,%36,%37,%38,%39,%40,%41,%42,%43,%44,%45,%46,%47,%48,%49,%50,%51,%52,%53,%54,%55,%56,%57,%58,%59,%60,%61,%62,%63}, %64, %65, p, 1, 1, %67, %68;\n}\n"
    : "+f"(d[0]),"+f"(d[1]),"+f"(d[2]),"+f"(d[3]),"+f"(d[4]),"+f"(d[5]),"+f"(d[6]),"+f"(d[7]),"+f"(d[8]),"+f"(d[9]),"+f"(d[10]),"+f"(d[11]),"+f"(d[12]),"+f"(d[13]),"+f"(d[14]),"+f"(d[15]),"+f"(d[16]),"+f"(d[17]),"+f"(d[18]),"+f"(d[19]),"+f"(d[20]),"+f"(d[21]),"+f"(d[22]),"+f"(d[23]),"+f"(d[24]),"+f"(d[25]),"+f"(d[26]),"+f"(d[27]),"+f"(d[28]),"+f"(d[29]),"+f"(d[30]),"+f"(d[31]),"+f"(d[32]),"+f"(d[33]),"+f"(d[34]),"+f"(d[35]),"+f"(d[36]),"+f"(d[37]),"+f"(d[38]),"+f"(d[39]),"+f"(d[40]),"+f"(d[41]),"+f"(d[42]),"+f"(d[43]),"+f"(d[44]),"+f"(d[45]),"+f"(d[46]),"+f"(d[47]),"+f"(d[48]),"+f"(d[49]),"+f"(d[50]),"+f"(d[51]),"+f"(d[52]),"+f"(d[53]),"+f"(d[54]),"+f"(d[55]),"+f"(d[56]),"+f"(d[57]),"+f"(d[58]),"+f"(d[59]),"+f"(d[60]),"+f"(d[61]),"+f"(d[62]),"+f"(d[63])
    : "l"(da), "l"(db), "r"(sc), "n"(TA), "n"(TB));
}
template <int TA, int TB>
__device__ __forceinline__ void wgmma_n160(float (&d)[80], uint64_t da, uint64_t db, int sc) {
  asm volatile("{\n.reg .pred p;\nsetp.ne.b32 p, %82, 0;\n"
    "wgmma.mma_async.sync.aligned.m64n160k16.f32.bf16.bf16 {%0,%1,%2,%3,%4,%5,%6,%7,%8,%9,%10,%11,%12,%13,%14,%15,%16,%17,%18,%19,%20,%21,%22,%23,%24,%25,%26,%27,%28,%29,%30,%31,%32,%33,%34,%35,%36,%37,%38,%39,%40,%41,%42,%43,%44,%45,%46,%47,%48,%49,%50,%51,%52,%53,%54,%55,%56,%57,%58,%59,%60,%61,%62,%63,%64,%65,%66,%67,%68,%69,%70,%71,%72,%73,%74,%75,%76,%77,%78,%79}, %80, %81, p, 1, 1, %83, %84;\n}\n"
    : "+f"(d[0]),"+f"(d[1]),"+f"(d[2]),"+f"(d[3]),"+f"(d[4]),"+f"(d[5]),"+f"(d[6]),"+f"(d[7]),"+f"(d[8]),"+f"(d[9]),"+f"(d[10]),"+f"(d[11]),"+f"(d[12]),"+f"(d[13]),"+f"(d[14]),"+f"(d[15]),"+f"(d[16]),"+f"(d[17]),"+f"(d[18]),"+f"(d[19]),"+f"(d[20]),"+f"(d[21]),"+f"(d[22]),"+f"(d[23]),"+f"(d[24]),"+f"(d[25]),"+f"(d[26]),"+f"(d[27]),"+f"(d[28]),"+f"(d[29]),"+f"(d[30]),"+f"(d[31]),"+f"(d[32]),"+f"(d[33]),"+f"(d[34]),"+f"(d[35]),"+f"(d[36]),"+f"(d[37]),"+f"(d[38]),"+f"(d[39]),"+f"(d[40]),"+f"(d[41]),"+f"(d[42]),"+f"(d[43]),"+f"(d[44]),"+f"(d[45]),"+f"(d[46]),"+f"(d[47]),"+f"(d[48]),"+f"(d[49]),"+f"(d[50]),"+f"(d[51]),"+f"(d[52]),"+f"(d[53]),"+f"(d[54]),"+f"(d[55]),"+f"(d[56]),"+f"(d[57]),"+f"(d[58]),"+f"(d[59]),"+f"(d[60]),"+f"(d[61]),"+f"(d[62]),"+f"(d[63]),"+f"(d[64]),"+f"(d[65]),"+f"(d[66]),"+f"(d[67]),"+f"(d[68]),"+f"(d[69]),"+f"(d[70]),"+f"(d[71]),"+f"(d[72]),"+f"(d[73]),"+f"(d[74]),"+f"(d[75]),"+f"(d[76]),"+f"(d[77]),"+f"(d[78]),"+f"(d[79])
    : "l"(da), "l"(db), "r"(sc), "n"(TA), "n"(TB));
}
template <int TA, int TB>
__device__ __forceinline__ void wgmma_n80(float (&d)[40], uint64_t da, uint64_t db, int sc) {
  asm volatile("{\n.reg .pred p;\nsetp.ne.b32 p, %42, 0;\n"
    "wgmma.mma_async.sync.aligned.m64n80k16.f32.bf16.bf16 {%0,%1,%2,%3,%4,%5,%6,%7,%8,%9,%10,%11,%12,%13,%14,%15,%16,%17,%18,%19,%20,%21,%22,%23,%24,%25,%26,%27,%28,%29,%30,%31,%32,%33,%34,%35,%36,%37,%38,%39}, %40, %41, p, 1, 1, %43, %44;\n}\n"
    : "+f"(d[0]),"+f"(d[1]),"+f"(d[2]),"+f"(d[3]),"+f"(d[4]),"+f"(d[5]),"+f"(d[6]),"+f"(d[7]),"+f"(d[8]),"+f"(d[9]),"+f"(d[10]),"+f"(d[11]),"+f"(d[12]),"+f"(d[13]),"+f"(d[14]),"+f"(d[15]),"+f"(d[16]),"+f"(d[17]),"+f"(d[18]),"+f"(d[19]),"+f"(d[20]),"+f"(d[21]),"+f"(d[22]),"+f"(d[23]),"+f"(d[24]),"+f"(d[25]),"+f"(d[26]),"+f"(d[27]),"+f"(d[28]),"+f"(d[29]),"+f"(d[30]),"+f"(d[31]),"+f"(d[32]),"+f"(d[33]),"+f"(d[34]),"+f"(d[35]),"+f"(d[36]),"+f"(d[37]),"+f"(d[38]),"+f"(d[39])
    : "l"(da), "l"(db), "r"(sc), "n"(TA), "n"(TB));
}

#define ELECT "{\n.reg .pred e;\nelect.sync _|e, 0xffffffff;\n@e "
__device__ __forceinline__ void mbar_init(uint32_t b, int c) { asm volatile("mbarrier.init.shared::cta.b64 [%0], %1;" ::"r"(b), "r"(c)); }
__device__ __forceinline__ void mbar_expect(uint32_t b, int bytes) { asm volatile(ELECT "mbarrier.arrive.expect_tx.shared::cta.b64 _, [%0], %1;\n}" ::"r"(b), "r"(bytes) : "memory"); }
__device__ __forceinline__ void mbar_arrive(uint32_t b) { asm volatile("mbarrier.arrive.shared::cta.b64 _, [%0];" ::"r"(b) : "memory"); }
__device__ __forceinline__ uint32_t mapa(uint32_t a, uint32_t cta) { uint32_t r; asm("mapa.shared::cluster.u32 %0, %1, %2;" : "=r"(r) : "r"(a), "r"(cta)); return r; }
__device__ __forceinline__ void mbar_wait(uint32_t b, uint32_t parity) {
  asm volatile("{\n.reg .pred p;\nW: mbarrier.try_wait.parity.shared::cta.b64 p, [%0], %1;\n@!p bra W;\n}\n" ::"r"(b), "r"(parity) : "memory");
}
__device__ __forceinline__ void mbar_wait_cluster(uint32_t b, uint32_t parity) {
  asm volatile("{\n.reg .pred p;\nW: mbarrier.try_wait.parity.acquire.cluster.shared::cta.b64 p, [%0], %1;\n@!p bra W;\n}\n" ::"r"(b), "r"(parity) : "memory");
}
__device__ __forceinline__ void mbar_wait_bounded(uint32_t b, uint32_t parity) {
  asm volatile(
      "{\n.reg .pred p;\n.reg .u32 c;\nmov.u32 c, 0;\n"
      "W: mbarrier.try_wait.parity.shared::cta.b64 p, [%0], %1, 1000;\n"
      "@p bra D;\n"
      "add.u32 c, c, 1;\nsetp.lt.u32 p, c, 0x400000;\n@p bra W;\ntrap;\n"
      "D:\n}\n" ::"r"(b), "r"(parity) : "memory");
}
__device__ __forceinline__ void tma2(uint32_t dst, const CUtensorMap* m, uint32_t bar, int c0, int c1) {
  asm volatile(ELECT "cp.async.bulk.tensor.2d.shared::cluster.global.mbarrier::complete_tx::bytes [%0], [%1, {%3,%4}], [%2];\n}"
               ::"r"(dst), "l"(m), "r"(bar), "r"(c0), "r"(c1) : "memory");
}
__device__ __forceinline__ void tma2_mc(uint32_t dst, const CUtensorMap* m, uint32_t bar, int c0, int c1) {
  asm volatile(ELECT "cp.async.bulk.tensor.2d.shared::cluster.global.mbarrier::complete_tx::bytes.multicast::cluster [%0], [%1, {%3,%4}], [%2], %5;\n}"
               ::"r"(dst), "l"(m), "r"(bar), "r"(c0), "r"(c1), "h"((uint16_t)3) : "memory");
}
__device__ __forceinline__ void tma3(uint32_t dst, const CUtensorMap* m, uint32_t bar, int c0, int c1, int c2) {
  asm volatile(ELECT "cp.async.bulk.tensor.3d.shared::cluster.global.mbarrier::complete_tx::bytes [%0], [%1, {%3,%4,%5}], [%2];\n}"
               ::"r"(dst), "l"(m), "r"(bar), "r"(c0), "r"(c1), "r"(c2) : "memory");
}
__device__ __forceinline__ void tma5(uint32_t dst, const CUtensorMap* m, uint32_t bar, int c0, int c1, int c2, int c3, int c4) {
  asm volatile(ELECT "cp.async.bulk.tensor.5d.shared::cluster.global.mbarrier::complete_tx::bytes [%0], [%1, {%3,%4,%5,%6,%7}], [%2];\n}"
               ::"r"(dst), "l"(m), "r"(bar), "r"(c0), "r"(c1), "r"(c2), "r"(c3), "r"(c4) : "memory");
}
__device__ __forceinline__ void tma2_pf(const CUtensorMap* m, int c0, int c1) {
  asm volatile(ELECT "cp.async.bulk.prefetch.tensor.2d.L2.global [%0, {%1,%2}];\n}" ::"l"(m), "r"(c0), "r"(c1) : "memory");
}
__device__ __forceinline__ void l2_prefetch(const void* p) { asm volatile("prefetch.global.L2 [%0];" ::"l"(p)); }
__device__ __forceinline__ uint64_t d64(uint32_t lo) { return (uint64_t)lo | (0x40000040ull << 32); }
__device__ __forceinline__ void arrive_if(uint32_t b, bool p) {
  asm volatile("{\n.reg .pred p;\nsetp.ne.b32 p, %1, 0;\n@p mbarrier.arrive.shared::cta.b64 _, [%0];\n}\n" ::"r"(b), "r"((int)p) : "memory");
}
__device__ __forceinline__ void arrive_cluster_if(uint32_t cluster_addr, bool p) {
  asm volatile("{\n.reg .pred p;\nsetp.ne.b32 p, %1, 0;\n@p mbarrier.arrive.shared::cluster.b64 _, [%0];\n}\n" ::"r"(cluster_addr), "r"((int)p) : "memory");
}
__device__ __forceinline__ int uni(int v) { return (int)__reduce_max_sync(~0u, (unsigned)v); }
__device__ __forceinline__ void wg_fence() { asm volatile("wgmma.fence.sync.aligned;" ::: "memory"); }
__device__ __forceinline__ void wg_commit() { asm volatile("wgmma.commit_group.sync.aligned;" ::: "memory"); }
template <int N> __device__ __forceinline__ void wg_wait() { asm volatile("wgmma.wait_group.sync.aligned %0;" ::"n"(N) : "memory"); }
template <int N> __device__ __forceinline__ void keep(float (&d)[N]) {
#pragma unroll
  for (int i = 0; i < N; i++) asm volatile("" : "+f"(d[i])::"memory");
}
__device__ __forceinline__ uint32_t pack_bf16(float lo, float hi) { uint32_t r; asm("cvt.rn.bf16x2.f32 %0, %1, %2;" : "=r"(r) : "f"(hi), "f"(lo)); return r; }
__device__ __forceinline__ float bf16r(float v) { return __bfloat162float(__float2bfloat16_rn(v)); }
__device__ __forceinline__ float lds_f(uint32_t a) { float v; asm volatile("ld.shared.f32 %0, [%1];" : "=f"(v) : "r"(a)); return v; }
__device__ __forceinline__ float4 lds_f4(uint32_t a) { float4 v; asm volatile("ld.shared.v4.f32 {%0,%1,%2,%3}, [%4];" : "=f"(v.x), "=f"(v.y), "=f"(v.z), "=f"(v.w) : "r"(a)); return v; }
__device__ __forceinline__ void stg4(void* p, uint32_t a, uint32_t b, uint32_t c, uint32_t d) {
  asm volatile("st.global.v4.b32 [%0], {%1,%2,%3,%4};" ::"l"(p), "r"(a), "r"(b), "r"(c), "r"(d) : "memory");
}
__device__ __forceinline__ uint2 lds_u2(uint32_t a) { uint2 v; asm volatile("ld.shared.v2.b32 {%0,%1}, [%2];" : "=r"(v.x), "=r"(v.y) : "r"(a)); return v; }
__device__ __forceinline__ uint32_t hmul2(uint32_t a, uint32_t b) { uint32_t r; asm("mul.rn.bf16x2 %0, %1, %2;" : "=r"(r) : "r"(a), "r"(b)); return r; }
__device__ __forceinline__ uint32_t hfma2(uint32_t a, uint32_t b, uint32_t c) { uint32_t r; asm("fma.rn.bf16x2 %0, %1, %2, %3;" : "=r"(r) : "r"(a), "r"(b), "r"(c)); return r; }
__device__ __forceinline__ uint32_t clock32() { uint32_t c; asm volatile("mov.u32 %0, %%clock;" : "=r"(c)); return c; }
template <int V> struct IntC { static constexpr int value = V; };
struct cf { float r, i; };
__device__ __forceinline__ cf cmul(cf a, cf b) { return {a.r * b.r - a.i * b.i, a.r * b.i + a.i * b.r}; }
__device__ __forceinline__ cf cfma(cf a, cf b, cf c) { return {fmaf(-a.i, b.i, fmaf(a.r, b.r, c.r)), fmaf(a.i, b.r, fmaf(a.r, b.i, c.i))}; }

template <bool SSM>
__device__ __forceinline__ void mainloop1(float (&a0)[64], float (&a1)[64], uint32_t sb, int rnd, uint32_t rel, bool swap, int lane) {
  const uint32_t bars = sb + SM_MISC;
  rnd = uni(rnd);
  if (!SSM) swap = uni(swap);
  if (rnd > 0) mbar_wait(bars + B_ORDER, (rnd - 1) & 1);
  const bool releaser = lane < 2;
  const uint32_t dbase = (sb & 0x3FFFF) >> 4;
  int it = rnd * 10;
#pragma unroll 1
  for (int kb = 0; kb < 10; kb++, it++) {
    const uint32_t slot = it & 3;
    uint32_t dw = dbase + (SM_RING >> 4) + slot * (XB >> 4), dx = dbase + kb * (XB >> 4);
    if (!SSM && swap) { const uint32_t t = dw; dw = dx; dx = t; }
    dx |= 1u << 16;
    dw |= 1u << 16;
    if (rnd < 2) mbar_wait(bars + B_XFULL + kb * 8, 0);
    mbar_wait(bars + B_FULL1 + slot * 8, (it >> 2) & 1);
    wg_fence();
#pragma unroll
    for (int kk = 0; kk < 4; kk++) {
      const int sc = (kb | kk) != 0;
      if (SSM) {
        wgmma_n128<0, 0>(a0, d64(dw + kk * 2), d64(dx + kk * 2), sc);
        wgmma_n128<0, 0>(a1, d64(dw + 512 + kk * 2), d64(dx + kk * 2), sc);
      } else {
        wgmma_n128<1, 0>(a0, d64(dw + kk * 128), d64(dx + kk * 2), sc);
        wgmma_n128<1, 0>(a1, d64(dw + 512 + kk * 128), d64(dx + kk * 2), sc);
      }
    }
    wg_commit();
    wg_wait<1>();
    arrive_cluster_if(rel + ((it - 1) & 3) * 8, releaser && kb > 0);
  }
  arrive_if(bars + B_ORDER, lane == 0);
  wg_wait<0>();
  keep(a0);
  keep(a1);
  arrive_cluster_if(rel + ((it - 1) & 3) * 8, releaser);
}

__device__ __forceinline__ void ffn_epilogue(float (&ag)[64], float (&au)[64], int rb, int u0, int lane) {
  __nv_bfloat16* dst = g_ht + (size_t)(1280 + u0) * L_ + rb * 128 + 8 * (lane & 3);
#pragma unroll
  for (int hi = 0; hi < 2; hi++)
#pragma unroll
    for (int k = 0; k < 4; k++) {
      uint32_t pk[4];
#pragma unroll
      for (int b = 0; b < 4; b++) {
        float v[2];
#pragma unroll
        for (int e = 0; e < 2; e++) {
          const int x = 4 * (4 * k + b) + 2 * hi + e;
          const float hz = 0.5f * ag[x], pu = hz * au[x];
          float th;
          asm("tanh.approx.f32 %0, %1;" : "=f"(th) : "f"(hz));
          v[e] = fmaf(pu, th, pu);
        }
        pk[b] = pack_bf16(v[0], v[1]);
      }
      stg4(dst + (size_t)(8 * hi) * L_ + 32 * k, pk[0], pk[1], pk[2], pk[3]);
    }
}

struct ChanPar { cf lam[2], coef[2], l32[2]; };
__device__ __forceinline__ float4 chan_params(float lr, float li, float ldt) {
  const float dt = bf16r(expf(ldt));
  const float e = expf(dt * lr);
  float s, co;
  sincospif(dt * li * 0.31830988618379067f, &s, &co);
  const float nr = e * co - 1.f, ni = e * s;
  const bool big = fabsf(lr) >= fabsf(li);
  const float a = big ? lr : li, b = big ? li : lr, t = __fdividef(b, a), inv = __fdividef(2.f, a + b * t);
  return make_float4(e * co, ni, (big ? nr + ni * t : nr * t + ni) * inv, (big ? ni - nr * t : ni * t - nr) * inv);
}

__device__ __forceinline__ cf shfl_up4(cf v, int d) { return {__shfl_up_sync(~0u, v.r, d, 4), __shfl_up_sync(~0u, v.i, d, 4)}; }
__device__ __forceinline__ cf shfl_dn4(cf v, int d) { return {__shfl_down_sync(~0u, v.r, d, 4), __shfl_down_sync(~0u, v.i, d, 4)}; }

__device__ __forceinline__ uint64_t tag_state(cf v, uint32_t tag) {
  return ((uint64_t)((__float_as_uint(v.i) & ~31u) | ((tag >> 5) & 31u)) << 32) | ((__float_as_uint(v.r) & ~31u) | (tag & 31u));
}
__device__ __forceinline__ bool ld_aggs(uint64_t (&v)[4][2], const uint4* src, int n, uint64_t tg) {
  uint64_t bad = 0;
#pragma unroll
  for (int u = 0; u < 4; u++) {
    v[u][0] = v[u][1] = tg;
    asm volatile("{\n.reg .pred p;\nsetp.gt.s32 p, %3, 0;\n@p ld.relaxed.gpu.global.v2.b64 {%0,%1}, [%2];\n}\n"
                 : "+l"(v[u][0]), "+l"(v[u][1]) : "l"(src - u * 320), "r"(n - u) : "memory");
  }
#pragma unroll
  for (int u = 0; u < 4; u++) bad |= (v[u][0] ^ tg) | (v[u][1] ^ tg);
  return (bad & 0x1f0000001full) == 0;
}

template <class V>
__device__ __forceinline__ void scan_store(cf s, cf lam, cf coef, __nv_bfloat16* dst, V v) {
  const uint32_t cr = pack_bf16(coef.r, coef.r), nci = pack_bf16(-coef.i, -coef.i), ncr = cr ^ 0x80008000u;
#pragma unroll
  for (int k = 0; k < 4; k++) {
    uint32_t pr[4], pi[4];
#pragma unroll
    for (int b = 0; b < 4; b++) {
      const cf s0 = cfma(lam, s, v(4 * k + b, 0));
      s = cfma(lam, s0, v(4 * k + b, 1));
      const uint32_t r2 = pack_bf16(s0.r, s.r), i2 = pack_bf16(s0.i, s.i);
      pr[b] = hfma2(cr, r2, hmul2(nci, i2));
      pi[b] = hfma2(ncr, i2, hmul2(nci, r2));
    }
    stg4(dst + 32 * k, pr[0], pr[1], pr[2], pr[3]);
    stg4(dst + (size_t)640 * L_ + 32 * k, pi[0], pi[1], pi[2], pi[3]);
  }
}

__device__ __forceinline__ void ssm_epilogue(float (&ar)[64], float (&ai)[64], const ChanPar& cp, int rb, int c0, int lane, uint32_t tag,
                                             uint32_t (&pend)[32], cf& e1) {
  const int q = lane & 3;
  cf h[2], e[2], l64[2];
#pragma unroll
  for (int hi = 0; hi < 2; hi++) h[hi] = {ar[2 * hi], ai[2 * hi]};
#pragma unroll
  for (int i = 1; i < 32; i++)
#pragma unroll
    for (int hi = 0; hi < 2; hi++) {
      const int x = 4 * (i >> 1) + 2 * hi + (i & 1);
      h[hi] = cfma(cp.lam[hi], h[hi], {ar[x], ai[x]});
    }
#pragma unroll
  for (int hi = 0; hi < 2; hi++) {
    l64[hi] = cmul(cp.l32[hi], cp.l32[hi]);
    cf t = shfl_up4(h[hi], 1);
    if (q >= 1) h[hi] = cfma(cp.l32[hi], t, h[hi]);
    t = shfl_up4(h[hi], 2);
    if (q >= 2) h[hi] = cfma(l64[hi], t, h[hi]);
  }
  const int rec = (c0 >> 4) * 8 + (c0 & 7);
  if (q == 3 && rb < 15)
    asm volatile("st.relaxed.gpu.global.v2.b64 [%0], {%1,%2};" ::"l"(g_agg + rb * 320 + rec), "l"(tag_state(h[0], tag)), "l"(tag_state(h[1], tag)) : "memory");
  const uint32_t t_pub = clock32();
#pragma unroll
  for (int x = 0; x < 16; x++) {
    pend[2 * x] = pack_bf16(ar[4 * x + 2], ar[4 * x + 3]);
    pend[2 * x + 1] = pack_bf16(ai[4 * x + 2], ai[4 * x + 3]);
  }
  cf l128[2], l512[2], l1024[2];
#pragma unroll
  for (int hi = 0; hi < 2; hi++) {
    const cf t = shfl_up4(h[hi], 1);
    e[hi] = q ? t : cf{0.f, 0.f};
    l128[hi] = cmul(l64[hi], l64[hi]);
    const cf l256 = cmul(l128[hi], l128[hi]);
    l512[hi] = cmul(l256, l256);
    l1024[hi] = cmul(l512[hi], l512[hi]);
  }
  if (rb > 0) {
    while (clock32() - t_pub < AGG_DELAY) __nanosleep(20);
    const uint4* src = g_agg + (rb - 1 - 4 * q) * 320 + rec;
    const uint64_t tg = tag_state({0.f, 0.f}, tag);
    uint64_t A[4][2];
    bool ok;
    do ok = ld_aggs(A, src, rb - 4 * q, tg);
    while (!__all_sync(~0u, ok));
#pragma unroll
    for (int hi = 0; hi < 2; hi++) {
      cf c = {0.f, 0.f};
#pragma unroll
      for (int u = 3; u >= 0; u--) {
        const cf a = {__uint_as_float((uint32_t)A[u][hi] & ~31u), __uint_as_float((uint32_t)(A[u][hi] >> 32) & ~31u)};
        c = u == 3 ? a : cfma(l128[hi], c, a);
      }
      cf t = shfl_dn4(c, 1);
      if (4 * q + 4 < rb) c = cfma(l512[hi], t, c);
      t = shfl_dn4(c, 2);
      if (rb > 8) c = cfma(l1024[hi], t, c);
      c = {__shfl_sync(~0u, c.r, 0, 4), __shfl_sync(~0u, c.i, 0, 4)};
      if (q & 1) c = cmul(c, cp.l32[hi]);
      if (q & 2) c = cmul(c, l64[hi]);
      e[hi].r += c.r;
      e[hi].i += c.i;
    }
  }
  scan_store(e[0], cp.lam[0], cp.coef[0], g_ht + (size_t)c0 * L_ + rb * 128 + 8 * q,
             [&](int x, int e2) { return cf{ar[4 * x + e2], ai[4 * x + e2]}; });
  e1 = e[1];
}

template <bool SSM>
__device__ __forceinline__ void mainloop2(float (&acc)[80], uint32_t sb, int i0, int i1, int first, int wg, bool releaser, int& slot, uint32_t& par) {
  const uint32_t bars = sb + SM_MISC;
  const uint32_t dbase = (sb & 0x3FFFF) >> 4;
#pragma unroll 1
  for (int i = i0; i < i1; i++) {
    const uint32_t ds = dbase + slot * (SLOT2 >> 4);
    const uint32_t da = (ds + wg * 512) | (1u << 16), db = (ds + (XB >> 4)) | ((SSM ? 1u : 512u) << 16);
    mbar_wait(bars + B_FULL2 + slot * 8, par);
    wg_fence();
#pragma unroll
    for (int kk = 0; kk < 4; kk++) {
      if (SSM) wgmma_n160<1, 0>(acc, d64(da + kk * 128), d64(db + kk * 2), kk != 0 || i != first);
      else wgmma_n160<1, 1>(acc, d64(da + kk * 128), d64(db + kk * 128), kk != 0 || i != first);
    }
    wg_commit();
    wg_wait<1>();
    arrive_if(bars + B_EMPTY2 + (slot ? slot - 1 : NS2 - 1) * 8, releaser && i > 0);
    if (++slot == NS2) { slot = 0; par ^= 1; }
  }
}

__device__ __forceinline__ void phase2(const Params& p, uint32_t sb, int rank, int t0, int nt, bool five, int wg, int w,
                                       int lane, int tid) {
  const uint32_t bars = sb + SM_MISC;
  five = uni(five);
  wg = uni(wg);
  const int nk = five ? 27 - NFB : 20 + NFB, n1 = wg ? nk - LEAD : nk;
  float acc[80], accs[80];
  if (wg == (int)five) mbar_wait(bars + B_ORDER, wg ^ 1);
  int slot = 0;
  uint32_t par = 0;
  mainloop2<false>(acc, sb, 0, five ? n1 : NFB, 0, wg, lane == 0, slot, par);
  if (!five) mainloop2<true>(accs, sb, NFB, n1, NFB, wg, lane == 0, slot, par);
  if (wg == 1) wg_wait<0>();
  arrive_if(wg == 0 ? bars + B_LEAD : bars + B_EMPTY2 + (slot ? slot - 1 : NS2 - 1) * 8, lane == 0);
  const int q = lane & 3;
  const bool odd = q & 1;
  const int ca = 80 * rank + 32 * (nt & 1) + (odd ? 6 + 2 * q : 2 * q), cb = ca - ((nt & rank & 1) ? 160 : 0);
  mbar_expect(bars + B_XCH + (wg * 4 + w) * 8, 2560);
  if (wg == 1) {
    mbar_wait(bars + B_LEAD, 0);
    if (five) mainloop2<false>(acc, sb, n1, nk, -1, wg, false, slot, par);
    else mainloop2<true>(accs, sb, n1, nk, -1, wg, false, slot, par);
  }
  mbar_wait(bars + B_GREADY, 0);
  const float g[2] = {lds_f(bars + M_G + (t0 & 127) * 4), lds_f(bars + M_G + (t0 & 127) * 4 + 128)};
  const float og[2] = {bf16r(1.f - g[0]), bf16r(1.f - g[1])};
  const uint32_t dst = mapa(sb + SM_XCH + (tid & ~3) * 16 + q * 8, rank ^ 1);
  const uint32_t bar = mapa(bars + B_XCH + (wg * 4 + w) * 8, rank ^ 1);
  mbar_wait(bars + B_XFREE, 0);
  wg_wait<0>();
  keep(acc);
  keep(accs);
  float z[40];
  auto halves = [&](auto RK) {
#pragma unroll
    for (int h = 0; h < 2; h++) {
      const int x0 = 40 * (h ? RK.value : 1 - RK.value);
      if (five) {
#pragma unroll
        for (int i = 0; i < 40; i++) z[i] = acc[x0 + i] * og[(i >> 1) & 1];
      } else {
#pragma unroll
        for (int i = 0; i < 40; i++) z[i] = fmaf(og[(i >> 1) & 1], acc[x0 + i], g[(i >> 1) & 1] * accs[x0 + i]);
      }
      if (h == 0) {
#pragma unroll
        for (int v = 0; v < 10; v++)
          asm volatile("st.async.weak.shared::cluster.mbarrier::complete_tx::bytes.v2.b32 [%0], {%1,%2}, [%3];"
                       ::"r"(dst + (v >> 1) * 4096 + (v & 1) * 32), "r"(pack_bf16(z[4 * v], z[4 * v + 1])),
                       "r"(pack_bf16(z[4 * v + 2], z[4 * v + 3])), "r"(bar) : "memory");
      }
    }
  };
  if (rank) halves(IntC<1>());
  else halves(IntC<0>());
  float4 y[5][2];
  mbar_wait(bars + B_XS, 0);
  const uint32_t xs = sb + (nk % NS2) * SLOT2 + (t0 & 127) * 320;
#pragma unroll
  for (int v = 0; v < 5; v++) {
    const uint2 dv = lds_u2(bars + M_PAR + (v < 3 ? ca : cb) * 2 + 32 * v);
#pragma unroll
    for (int hi = 0; hi < 2; hi++) {
      const uint2 xv = lds_u2(xs + (v < 3 ? ca : cb) * 2 + 32 * 320 * hi + 32 * v);
      const int x = 8 * v + 2 * hi;
      const float s0 = __shfl_xor_sync(~0u, odd ? z[x] : z[x + 4], 1), s1 = __shfl_xor_sync(~0u, odd ? z[x + 1] : z[x + 5], 1);
      const uint32_t d0 = hmul2(xv.x, dv.x), d1 = hmul2(xv.y, dv.y);
      y[v][hi].x = fmaf(g[hi], __uint_as_float(d0 << 16), odd ? s0 : z[x]);
      y[v][hi].y = fmaf(g[hi], __uint_as_float(d0 & 0xffff0000u), odd ? s1 : z[x + 1]);
      y[v][hi].z = fmaf(g[hi], __uint_as_float(d1 << 16), odd ? z[x + 4] : s0);
      y[v][hi].w = fmaf(g[hi], __uint_as_float(d1 & 0xffff0000u), odd ? z[x + 5] : s1);
    }
  }
  float* o = p.out + (size_t)t0 * D_ + nt * 160;
  const uint32_t src = sb + SM_XCH + (tid & ~3) * 16 + (odd ? 32 + (q - 1) * 8 : q * 8);
  mbar_wait_cluster(bars + B_XCH + (wg * 4 + w) * 8, 0);
  arrive_if(bars + B_DONE, lane == 0);
#pragma unroll
  for (int v = 0; v < 5; v++) {
    uint32_t u[4];
    asm volatile("ld.shared.v4.b32 {%0,%1,%2,%3}, [%4];" : "=r"(u[0]), "=r"(u[1]), "=r"(u[2]), "=r"(u[3]) : "r"(src + v * 4096));
#pragma unroll
    for (int hi = 0; hi < 2; hi++)
      *reinterpret_cast<float4*>(o + (v < 3 ? ca : cb) + 32 * hi * D_ + 16 * v) =
          make_float4(y[v][hi].x + __uint_as_float(u[hi] << 16), y[v][hi].y + __uint_as_float(u[hi] & 0xffff0000u),
                      y[v][hi].z + __uint_as_float(u[2 + hi] << 16), y[v][hi].w + __uint_as_float(u[2 + hi] & 0xffff0000u));
  }
}

__device__ __forceinline__ int tile_of(int j, bool five, int rnd) {
  return rnd == 0 ? j : rnd == 1 ? (j >= 4 ? 8 + j : (five ? 8 : 10) + (j >> 1)) : rnd == 4 ? 32 + (j >> 1) : 8 * rnd + j;
}

__device__ __forceinline__ int kblock_of(bool five, int i) {
  if (!five) return i < NFB ? 20 + i : ((i - NFB) >> 1) + 10 * ((i - NFB) & 1);
  const int c = i + NFB;
  return c < 14 ? 20 + c : 34 + (int)((0x98ba3210c7654ull >> (4 * (c - 14))) & 15);
}

__device__ __forceinline__ uint32_t ld_epoch(uint32_t bars) {
  uint32_t tag;
  asm volatile("ld.shared.u32 %0, [%1];" : "=r"(tag) : "r"(bars + M_EPOCH) : "memory");
  return tag;
}

__device__ __forceinline__ void cluster_arrive() { asm volatile("barrier.cluster.arrive.relaxed.aligned;" ::: "memory"); }
__device__ __forceinline__ void cluster_wait() { asm volatile("barrier.cluster.wait.aligned;" ::: "memory"); }
__device__ __forceinline__ void map_prefetch(const CUtensorMap* m) { asm volatile("prefetch.tensormap [%0];" ::"l"(m) : "memory"); }

__global__ void __cluster_dims__(2, 1, 1) __launch_bounds__(384, 1) fused_kernel(const __grid_constant__ Params p) {
  extern __shared__ __align__(1024) uint8_t smem_raw[];
  const uint32_t sb = (uint32_t)__cvta_generic_to_shared(smem_raw);
  const uint32_t bars = sb + SM_MISC;
  const int tid = threadIdx.x, warp = uni(tid >> 5), lane = tid & 31;
  const int rank = blockIdx.x & 1, pair = blockIdx.x >> 1;
  const int ps = pair < 4 ? 4 + pair : pair < 36 ? ((pair - 4) & 7) * 8 + ((pair - 4) >> 3)
               : pair < 64 ? (1 + (pair - 36) % 7) * 8 + 4 + (pair - 36) / 7 : pair;
  const bool spare = ps >= 64;
  const int j = ps & 7, sg = ps >> 3;
  const int rb = spare ? ((ps & 1) * 2 + rank) * 4 : (ps >> 3) * 2 + rank;
  const int rb2 = (ps >> 3) * 2 + (j >> 2);
  const bool five = !spare && rank == (j & 1);
  const int nt1 = five ? 5 : 4;

  auto first_fill = [&](int kb) {
    const uint32_t dx = spare ? SM_RING : 0, bx = spare ? B_FULL1 : B_XFULL, bw = bars + B_FULL1 - bx + kb * 8;
    const int c0 = spare ? 26 * 64 : kb * 64, c1 = spare ? kb * 64 : j * 64;
    mbar_expect(bars + bx + kb * 8, XB);
    tma5(sb + dx + kb * XB, &p.x, bars + bx + kb * 8, kb * 64, 0, 0, 0, rb);
    mbar_expect(bw, XB);
    tma2(sb + SM_RING - dx + kb * XB, spare ? &p.wg : &p.bre, bw, c0, c1);
    tma2(sb + SM_RING - dx + kb * XB + 8192, spare ? &p.wu : &p.bim, bw, c0, c1);
  };

  if (warp >= 8) {
    asm volatile("setmaxnreg.dec.sync.aligned.u32 40;");
    if (warp == 8) {
      if (lane == 0) {
#pragma unroll
        for (int i = 1; i < 14; i++)
          if (i != 10) mbar_init(bars + B_XFULL + i * 8, 1);
        asm volatile("fence.mbarrier_init.release.cluster;" ::: "memory");
      }
      __syncwarp();
      asm volatile("bar.arrive 1, 384;" ::: "memory");
#pragma unroll
      for (int kb = 1; kb < 4; kb++) first_fill(kb);
      cluster_arrive();
      const int n1 = nt1 * 10;
      mbar_expect(bars + B_XFULL + 32, XB);
      if (!spare) {
        tma5(sb + 4 * XB, &p.x, bars + B_XFULL + 32, 4 * 64, 0, 0, 0, rb);
        if (sg < 6) tma2_pf(rank ? &p.bim : &p.bre, (4 + sg) * 64, j * 64);
        if (sg < 4) {
          const int t = tile_of(j, five, 1), half = j < 4 ? j & 1 : rank;
          if (t < 10) tma2_pf(&p.bre + half, sg * 64, t * 64);
          else tma2_pf(&p.wg + half, (t - 10) * 64, sg * 64);
        }
      } else {
        tma2(sb + 4 * XB, &p.wg, bars + B_XFULL + 32, 26 * 64, 4 * 64);
        tma2(sb + 4 * XB + 8192, &p.wu, bars + B_XFULL + 32, 26 * 64, 4 * 64);
      }
      cluster_wait();
      const uint32_t ring = sb + SM_RING;
      if (spare) {
#pragma unroll 1
        for (int it = 4, kb = 4, r = rb; it < 40; it++) {
          const uint32_t sl = it & 3, fb = bars + B_FULL1 + sl * 8;
          mbar_wait(bars + B_EMPTY1 + sl * 8, ((it >> 2) & 1) ^ 1);
          mbar_expect(fb, XB);
          tma5(ring + sl * XB, &p.x, fb, kb * 64, 0, 0, 0, r);
          if (it < 9) {
            const uint32_t xb = bars + B_XFULL + (it + 1) * 8, xd = sb + (it + 1) * XB;
            mbar_expect(xb, XB);
            tma2(xd, &p.wg, xb, 26 * 64, (it + 1) * 64);
            tma2(xd + 8192, &p.wu, xb, 26 * 64, (it + 1) * 64);
          }
          if (++kb == 10) { kb = 0; r++; }
        }
      } else {
        const int nk = five ? 27 - NFB : 20 + NFB, n0 = (j & 3) * 160;
        const int na = n0 + (j & 1) * 32, nh = n0 + ((j & 1) ? 0 : 128);
        int it = 4;
#pragma unroll 1
        for (int rnd = 0; rnd < 4; rnd++) {
          const int t = tile_of(j, five, rnd), tn = tile_of(j, five, rnd + 1);
          const bool own = rnd == 1 && j < 4, ownn = rnd == 3 || (rnd == 0 && j < 4);
          const CUtensorMap *m = (t < 10 ? &p.bre : &p.wg) + (own ? 0 : rank), *mn = (tn < 10 ? &p.bre : &p.wg) + (ownn ? j & 1 : rank);
          const int s0 = t < 10 ? 64 : 0, sn0 = tn < 10 ? 64 : 0, pf = rnd < 3 || five ? sg : 8;
          const int f0 = t < 10 ? 0 : (t - 10) * 64, f1 = t < 10 ? t * 64 : 0, g0 = tn < 10 ? 0 : (tn - 10) * 64, g1 = tn < 10 ? tn * 64 : 0;
#pragma unroll 1
          for (int kb = it - rnd * 10; kb < 10; kb++, it++) {
            const uint32_t sl = it & 3, fb = bars + B_FULL1 + sl * 8;
            mbar_wait(bars + B_EMPTY1 + sl * 8, ((it >> 2) & 1) ^ 1);
            mbar_expect(fb, XB);
            if (own) {
              tma2(ring + sl * XB, m, fb, f0 + kb * s0, f1 + kb * (64 - s0));
              tma2(ring + sl * XB + 8192, m + 1, fb, f0 + kb * s0, f1 + kb * (64 - s0));
            } else {
              tma2_mc(ring + sl * XB + rank * 8192, m, fb, f0 + kb * s0, f1 + kb * (64 - s0));
            }
            if (it < 9) {
              mbar_expect(bars + B_XFULL + (it + 1) * 8, XB);
              tma5(sb + (it + 1) * XB, &p.x, bars + B_XFULL + (it + 1) * 8, (it + 1) * 64, 0, 0, 0, rb);
            }
            if ((it & 7) == pf) tma2_pf(mn, g0 + kb * sn0, g1 + kb * (64 - sn0));
          }
        }
        if (five) {
          const int c0 = (22 + (j >> 1)) * 64;
#pragma unroll 1
          for (; it < 50; it++) {
            const uint32_t sl = it & 3, fb = bars + B_FULL1 + sl * 8;
            mbar_wait(bars + B_EMPTY1 + sl * 8, ((it >> 2) & 1) ^ 1);
            mbar_expect(fb, XB);
            tma2(ring + sl * XB, &p.wg, fb, c0, (it - 40) * 64);
            tma2(ring + sl * XB + 8192, &p.wu, fb, c0, (it - 40) * 64);
          }
        }
        int slot = 0;
        uint32_t par = 1, nready = 0;
#pragma unroll 1
        for (int i = 0; i < nk; i++) {
          const int kbid = kblock_of(five, i);
          if (i >= NS2) mbar_wait(bars + B_EMPTY2 + slot * 8, par);
          else if (i == 2 || i == 3) mbar_wait(bars + B_EMPTY1 + ((n1 + 2 * i - 7) & 3) * 8, ((n1 + 2 * i - 7) >> 2) & 1);
          if (i == NS2 && five && j >= 4) {
            const uint32_t c0 = clock32();
            while (clock32() - c0 < REL) {}
          }
          while (nready <= i) {
            asm volatile("ld.acquire.cta.shared.u32 %0, [%1];" : "=r"(nready) : "r"(bars + M_NREADY) : "memory");
            nready = uni(nready);
          }
          const uint32_t st = sb + slot * SLOT2, fb = bars + B_FULL2 + slot * 8;
          if (kbid < 20) {
            const int im = kbid >= 10, k0 = (kbid - 10 * im) * 64;
            mbar_expect(fb, XB + 20480);
            tma3(st, &p.ht, fb, 0, kbid * 64, rb2 * 2);
            tma2(st + XB, &p.c128[im], fb, k0, na);
            tma2(st + 2 * XB, &p.c32[im], fb, k0, nh);
          } else {
            mbar_expect(fb, SLOT2);
            tma3(st, &p.ht, fb, 0, kbid * 64, rb2 * 2);
            tma3(st + XB, &p.wd, fb, 0, (kbid - 20) * 64, na >> 6);
            tma2(st + 2 * XB, &p.wdh[j & 3], fb, nh, (kbid - 20) * 64);
          }
          if (++slot == NS2) { slot = 0; par ^= 1; }
        }
        mbar_wait(bars + B_EMPTY2 + slot * 8, par);
        mbar_expect(bars + B_XS, SLOT2 + 320);
        tma2(sb + slot * SLOT2, &p.xs, bars + B_XS, n0, rb2 * 128);
        asm volatile(ELECT "cp.async.bulk.shared::cluster.global.mbarrier::complete_tx::bytes [%0], [%1], 320, [%2];\n}"
                     ::"r"(bars + M_PAR), "l"(p.dskip + n0), "r"(bars + B_XS) : "memory");
      }
    } else {
      if (tid == 288) {
#pragma unroll
        for (int i = 0; i < 4; i++) mbar_init(bars + B_EMPTY1 + i * 8, 8);
#pragma unroll
        for (int i = 0; i < NS2; i++) { mbar_init(bars + B_FULL2 + i * 8, 1); mbar_init(bars + B_EMPTY2 + i * 8, 8); }
        mbar_init(bars + B_XFREE, 8);
        mbar_init(bars + B_GREADY, 1);
        mbar_init(bars + B_ORDER, 4);
        asm volatile("fence.mbarrier_init.release.cluster;" ::: "memory");
      } else if (tid == 320) {
        if (sb & 1023) __trap();
#pragma unroll
        for (int i = 0; i < 8; i++) mbar_init(bars + B_XCH + i * 8, 1);
#pragma unroll
        for (int i = 0; i < 5; i++) mbar_init(bars + B_PUB + i * 8, 4);
        mbar_init(bars + B_EPOCH, 1);
        mbar_init(bars + B_DONE, 8);
        mbar_init(bars + B_PAR, 4);
        mbar_init(bars + B_LEAD, 4);
        mbar_init(bars + B_XS, 1);
        asm volatile("st.shared.u32 [%0], %1;" ::"r"(bars + M_NREADY), "r"(0) : "memory");
        asm volatile("fence.mbarrier_init.release.cluster;" ::: "memory");
      }
      __syncwarp();
      asm volatile("bar.sync 1, 384;" ::: "memory");
      cluster_arrive();
      if (warp == 9) {
        uint32_t tag = 0;
        if (lane == 0) {
          tag = (uint32_t)(atomicAdd(&g_ticket, 1ull) / NCTA) + 1u;
          asm volatile("st.shared.u32 [%0], %1;" ::"r"(bars + M_EPOCH), "r"(tag) : "memory");
          mbar_arrive(bars + B_EPOCH);
        }
        tag = __shfl_sync(~0u, tag, 0);
        if (!spare) {
          if (lane < 10) map_prefetch(lane < 9 ? &p.wg + lane : &p.wdh[j & 3]);
          const int nk = five ? 27 - NFB : 20 + NFB, kbid = kblock_of(five, lane < nk ? lane : 0);
          const unsigned* flag = g_cnt + rb2 * 64 + (kbid < 10 ? kbid : kbid - 10);
          int nready = 0, spins = 0;
          mbar_wait_bounded(bars + B_PUB, 0);
          while (nready < nk) {
            uint32_t v;
            asm volatile("ld.acquire.gpu.global.u32 %0, [%1];" : "=r"(v) : "l"(flag) : "memory");
            const int n = __ffs(__ballot_sync(~0u, v != tag || lane >= nk)) - 1;
            if (n > nready) {
              nready = n;
              asm volatile("fence.proxy.async.global;" ::: "memory");
              __syncwarp();
              if (lane == 0) asm volatile("st.release.cta.shared.u32 [%0], %1;" ::"r"(bars + M_NREADY), "r"(n) : "memory");
            } else {
              __nanosleep(200);
            }
            if (++spins > (1 << 20)) __trap();
          }
        }
        mbar_wait_bounded(bars + B_DONE, 0);
      } else {
        const uint32_t tag = (mbar_wait_bounded(bars + B_EPOCH, 0), ld_epoch(bars));
        if (warp == 11 && !spare) {
          const int cta = rb * 8 + j;
          mbar_wait_bounded(bars + B_XFULL + 72, 0);
#pragma unroll 1
          for (int i = lane; i < 135; i += 32) l2_prefetch(p.pwd + (size_t)cta * 5 * F_ + i * 64);
          const uint2* src = g_gate + rb2 * 128 + lane * 4;
          uint64_t v0, v1, v2, v3;
          int spins = 0;
          bool ok;
          do {
            __nanosleep(1000);
            asm volatile("ld.relaxed.gpu.global.v2.b64 {%0,%1}, [%2];" : "=l"(v0), "=l"(v1) : "l"(src) : "memory");
            asm volatile("ld.relaxed.gpu.global.v2.b64 {%0,%1}, [%2];" : "=l"(v2), "=l"(v3) : "l"(src + 2) : "memory");
            ok = (uint32_t)(v0 >> 32) == tag && (uint32_t)(v1 >> 32) == tag && (uint32_t)(v2 >> 32) == tag && (uint32_t)(v3 >> 32) == tag;
            if (++spins > (1 << 20)) __trap();
          } while (!__all_sync(~0u, ok));
          asm volatile("st.shared.v4.b32 [%0], {%1,%2,%3,%4};" ::"r"(bars + M_G + lane * 16),
                       "r"((uint32_t)v0), "r"((uint32_t)v1), "r"((uint32_t)v2), "r"((uint32_t)v3) : "memory");
          __syncwarp();
          if (lane == 0) mbar_arrive(bars + B_GREADY);
          __nanosleep(2000);
#pragma unroll 1
          for (int i = lane; i < 100; i += 32) l2_prefetch((i < 50 ? p.pcre : p.pcim - 3200) + (size_t)cta * 3200 + i * 64);
        }
#pragma unroll 1
        for (int rnd = warp - 10; rnd < nt1; rnd += 2) {
          mbar_wait_bounded(bars + B_PUB + rnd * 8, 0);
          if (lane == 0) {
            unsigned* flag = spare ? g_cnt + (rb + rnd) * 64 + 36 : g_cnt + rb * 64 + tile_of(j, five, rnd);
            asm volatile("st.release.gpu.global.u32 [%0], %1;" ::"l"(flag), "r"(tag) : "memory");
          }
          __syncwarp();
        }
      }
      cluster_wait();
    }
  } else {
    if (warp == 0) {
      if (lane == 0) {
        mbar_init(bars + B_XFULL, 1);
        mbar_init(bars + B_FULL1, 1);
        asm volatile("fence.mbarrier_init.release.cluster;" ::: "memory");
      }
      __syncwarp();
      first_fill(0);
    }
    asm volatile("setmaxnreg.inc.sync.aligned.u32 232;");
    asm volatile("bar.sync 1, 384;" ::: "memory");
    cluster_arrive();
    const int wg = warp >> 2, w = warp & 3;
    if (!spare && wg == 1) {
      const int c = (w < 2 || j >= 4 ? j : 8 + (j >> 1)) * 64 + (tid & 63);
      const float4 cp = chan_params(__bfloat162float(p.lre[c]), __bfloat162float(p.lim[c]), __bfloat162float(p.ldt[c]));
      asm volatile("st.shared.v4.f32 [%0], {%1,%2,%3,%4};" ::"r"(bars + M_PAR + (tid - 128) * 16), "f"(cp.x), "f"(cp.y), "f"(cp.z), "f"(cp.w) : "memory");
      mbar_wait(bars + B_XFULL, 0);
      const uint4* xr = reinterpret_cast<const uint4*>(p.px + (size_t)(rb * 128 + j * 16 + w * 4 + (lane >> 3)) * D_) + (lane & 7);
      const uint4* gr = reinterpret_cast<const uint4*>(p.gw) + (lane & 7);
      uint4 xa[10], ga[10];
#pragma unroll
      for (int i = 0; i < 10; i++) { xa[i] = xr[8 * i]; ga[i] = gr[8 * i]; }
      const int t = rb * 128 + j * 16 + w * 4 + (lane >> 3);
      float z = 0.f;
#pragma unroll
      for (int i = 0; i < 10; i++) {
        const uint32_t pr[4] = {hmul2(xa[i].x, ga[i].x), hmul2(xa[i].y, ga[i].y), hmul2(xa[i].z, ga[i].z), hmul2(xa[i].w, ga[i].w)};
#pragma unroll
        for (int e = 0; e < 4; e++) z += __uint_as_float(pr[e] << 16) + __uint_as_float(pr[e] & 0xffff0000u);
      }
      z += __shfl_xor_sync(~0u, z, 1);
      z += __shfl_xor_sync(~0u, z, 2);
      z += __shfl_xor_sync(~0u, z, 4);
      const float g = bf16r(__fdividef(1.f, 1.f + __expf(-bf16r(z))));
      mbar_wait(bars + B_EPOCH, 0);
      if ((lane & 7) == 0)
        asm volatile("st.relaxed.gpu.global.b64 [%0], %1;" ::"l"(g_gate + t), "l"(((uint64_t)ld_epoch(bars) << 32) | __float_as_uint(g)) : "memory");
      __syncwarp();
      arrive_if(bars + B_PAR, lane == 0);
    }
    cluster_wait();
    const uint32_t rel_own = mapa(bars + B_EMPTY1, rank), rel_mc = mapa(bars + B_EMPTY1, spare ? rank : rank ^ (lane & 1));
    int rnd = wg;
    bool pending = !spare && (wg == 0 || (j < 4 && five));
    const int cb = wg ? 8 + (j >> 1) : j;
    const int cl = 16 * w + (lane >> 2);
    uint32_t pend[32];
    cf e1;
    if (pending) {
      float a0[64], a1[64];
      mainloop1<true>(a0, a1, sb, rnd, rel_mc, false, lane);
      mbar_wait(bars + B_PAR, 0);
      const float4 p0 = lds_f4(bars + M_PAR + (64 * wg + cl) * 16), p1 = lds_f4(bars + M_PAR + (64 * wg + cl + 8) * 16);
      ChanPar cp = {{{p0.x, p0.y}, {p1.x, p1.y}}, {{p0.z, p0.w}, {p1.z, p1.w}}, {{p0.x, p0.y}, {p1.x, p1.y}}};
#pragma unroll
      for (int k = 0; k < 5; k++) { cp.l32[0] = cmul(cp.l32[0], cp.l32[0]); cp.l32[1] = cmul(cp.l32[1], cp.l32[1]); }
      ssm_epilogue(a0, a1, cp, rb, cb * 64 + cl, lane, ld_epoch(bars), pend, e1);
      rnd += 2;
    }
    const int t0 = rb2 * 128 + 64 * (w & 1) + 8 * (2 * wg + (w >> 1)) + (lane >> 2);
#pragma unroll 1
    for (; rnd < nt1; rnd += 2) {
      float a0[64], a1[64];
      mainloop1<false>(a0, a1, sb, rnd, rnd < 4 ? rel_mc : rel_own, spare, lane);
      if (rnd + 2 >= nt1 && !spare) arrive_cluster_if(mapa(bars + B_XFREE, rank ^ 1), lane == 0);
      if (pending) {
        const float4 p1 = lds_f4(bars + M_PAR + (64 * wg + cl + 8) * 16);
        scan_store(e1, {p1.x, p1.y}, {p1.z, p1.w}, g_ht + (size_t)(cb * 64 + cl + 8) * L_ + rb * 128 + 8 * (lane & 3),
                   [&](int x, int e2) {
                     return e2 ? cf{__uint_as_float(pend[2 * x] & 0xffff0000u), __uint_as_float(pend[2 * x + 1] & 0xffff0000u)}
                               : cf{__uint_as_float(pend[2 * x] << 16), __uint_as_float(pend[2 * x + 1] << 16)};
                   });
        __syncwarp();
        arrive_if(bars + B_PUB + wg * 8, lane == 0);
        pending = false;
      }
      ffn_epilogue(a0, a1, spare ? rb + rnd : rb, (spare ? 26 : tile_of(j, five, rnd) - 10) * 64 + cl, lane);
      __syncwarp();
      arrive_if(bars + B_PUB + rnd * 8, lane == 0);
    }
    if (!spare) phase2(p, sb, rank, t0, j & 3, five, wg, w, lane, tid);
    if (spare) arrive_if(bars + B_DONE, lane == 0);
  }
}

typedef CUresult (*EncodeFn)(CUtensorMap*, CUtensorMapDataType, cuuint32_t, void*, const cuuint64_t*, const cuuint64_t*, const cuuint32_t*,
                             const cuuint32_t*, CUtensorMapInterleave, CUtensorMapSwizzle, CUtensorMapL2promotion, CUtensorMapFloatOOBfill);

void make_map(EncodeFn enc, CUtensorMap* m, const void* base, int rank, const cuuint64_t* dims, const cuuint64_t* strides, const cuuint32_t* box,
              CUtensorMapSwizzle sw = CU_TENSOR_MAP_SWIZZLE_128B) {
  const cuuint32_t es[5] = {1, 1, 1, 1, 1};
  enc(m, CU_TENSOR_MAP_DATA_TYPE_BFLOAT16, rank, const_cast<void*>(base), dims, strides, box, es, CU_TENSOR_MAP_INTERLEAVE_NONE,
      sw, CU_TENSOR_MAP_L2_PROMOTION_L2_128B, CU_TENSOR_MAP_FLOAT_OOB_FILL_NONE);
}

}

extern "C" void kernel_launch(void* const* d_in, const int* in_sizes, int n_in, void* d_out, int out_size) {
  static EncodeFn enc = nullptr;
  static void* ht = nullptr;
  if (!enc) {
    void* fn = nullptr;
    cudaDriverEntryPointQueryResult qr;
    cudaGetDriverEntryPoint("cuTensorMapEncodeTiled", &fn, cudaEnableDefault, &qr);
    enc = (EncodeFn)fn;
    cudaGetSymbolAddress(&ht, g_ht);
    cudaFuncSetAttribute(fused_kernel, cudaFuncAttributeMaxDynamicSharedMemorySize, SMEM_BYTES);
  }
  typedef const __nv_bfloat16* bp;
  Params p;
  p.px = (bp)d_in[0]; p.lre = (bp)d_in[1]; p.lim = (bp)d_in[2]; p.pbre = (bp)d_in[3]; p.pbim = (bp)d_in[4];
  p.pcre = (bp)d_in[5]; p.pcim = (bp)d_in[6]; p.ldt = (bp)d_in[7]; p.dskip = (bp)d_in[8];
  p.pwg = (bp)d_in[10]; p.pwu = (bp)d_in[11]; p.pwd = (bp)d_in[12]; p.gw = (bp)d_in[13];
  p.out = (float*)d_out;
  {
    const cuuint64_t d[5] = {640, 2, 4, 16, 16}, s[4] = {1280, 32 * 1280, 2 * 1280, 128 * 1280};
    const cuuint32_t b[5] = {64, 2, 4, 16, 1};
    make_map(enc, &p.x, p.px, 5, d, s, b);
  }
  {
    const cuuint64_t d[2] = {640, 640}, s[1] = {1280};
    const cuuint32_t b[2] = {64, 64}, b128[2] = {64, 128}, b32[2] = {64, 32};
    make_map(enc, &p.bre, p.pbre, 2, d, s, b);
    make_map(enc, &p.bim, p.pbim, 2, d, s, b);
    make_map(enc, &p.c128[0], p.pcre, 2, d, s, b128);
    make_map(enc, &p.c128[1], p.pcim, 2, d, s, b128);
    make_map(enc, &p.c32[0], p.pcre, 2, d, s, b32);
    make_map(enc, &p.c32[1], p.pcim, 2, d, s, b32);
  }
  {
    const cuuint64_t d[2] = {1728, 640}, s[1] = {3456};
    const cuuint32_t b[2] = {64, 64};
    make_map(enc, &p.wg, p.pwg, 2, d, s, b);
    make_map(enc, &p.wu, p.pwu, 2, d, s, b);
  }
  {
    const cuuint64_t d[3] = {64, 3008, 32}, s[2] = {L_ * 2, 128};
    const cuuint32_t b[3] = {64, 64, 2};
    make_map(enc, &p.ht, ht, 3, d, s, b);
  }
  {
    const cuuint64_t d[2] = {640, 2048}, s[1] = {1280};
    const cuuint32_t b[2] = {160, 128};
    make_map(enc, &p.xs, p.px, 2, d, s, b, CU_TENSOR_MAP_SWIZZLE_NONE);
  }
  {
    const cuuint64_t d[3] = {64, 1728, 10}, s[2] = {1280, 128};
    const cuuint32_t b[3] = {64, 64, 2}, bh[2] = {64, 64};
    make_map(enc, &p.wd, p.pwd, 3, d, s, b);
    for (int nt = 0; nt < 4; nt++) {
      const cuuint64_t dh[2] = {(cuuint64_t)(nt * 160 + ((nt & 1) ? 32 : 160)), 1728};
      make_map(enc, &p.wdh[nt], p.pwd, 2, dh, s, bh);
    }
  }
  fused_kernel<<<NCTA, 384, SMEM_BYTES, cudaStreamPerThread>>>(p);
}
```
